```python
import torch

def _softmax(x, axis=-1):
    return torch.softmax(x, dim=axis)
def _gelu(x):
    return torch.nn.functional.gelu(x, approximate="tanh")
def _silu(x):
    return torch.nn.functional.silu(x)
def _sigmoid(x):
    return torch.sigmoid(x)
def _layernorm(x, axis=-1, eps=1e-5):
    m = x.mean(dim=axis, keepdim=True)
    v = x.var(dim=axis, keepdim=True, unbiased=False)
    return (x - m) / torch.sqrt(v + eps)
def _scatter_add(tgt, idx, src, axis=0):
    return tgt.clone().index_add_(axis, idx, src)
def _segment_sum(src, seg, n):
    out = torch.zeros((n,) + src.shape[1:], dtype=src.dtype)
    return out.index_add_(0, seg, src)
def _pad(x, pw):
    flat = tuple(v for pair in reversed(pw) for v in pair)
    return torch.nn.functional.pad(x, flat)

kernel_name = 'interleave_layers__gqa_block_cached__glu_gated_bilinear__decode'

def setup_inputs():

    _w = (lambda a: (lambda t: t.to(torch.bfloat16) if t.is_floating_point() else t)(torch.as_tensor(a)))
    def _A_setup():
        B, Sq, D = 2, 1, 512
        Hq, Hkv, Sk, Dh = 32, 32, 16384, 128
        assert Hq % Hkv == 0, (Hq, Hkv)
        return {
            "x": _w((lambda *s: torch.randn(*s, dtype=torch.bfloat16) * 0.05)(B, Sq, D)),
            "k_cache": _w((lambda *s: torch.randn(*s, dtype=torch.bfloat16) * 0.8)(B, Hkv, Sk, Dh)),
            "v_cache": _w((lambda *s: torch.randn(*s, dtype=torch.bfloat16) * 1.6)(B, Hkv, Sk, Dh)),
            "wq": _w((lambda *s: torch.randn(*s, dtype=torch.bfloat16) * 0.8)(D, Hq * Dh) * (D ** -0.5)),
            "wo": _w((lambda *s: torch.randn(*s, dtype=torch.bfloat16) * 1.6)(Hq * Dh, D) * ((Hq * Dh) ** -0.5)),
        }
    _A_in = _A_setup()

    def _B_setup():
        B, S, D, F = 2, 1, 512, 1376
        return {
            "x": _w((lambda *s: torch.randn(*s, dtype=torch.bfloat16) * 0.05)(B, S, D)),
            "w_gate": _w((lambda *s: torch.randn(*s, dtype=torch.bfloat16) * 0.4)(D, F) * (D ** -0.5)),
            "w_up": _w((lambda *s: torch.randn(*s, dtype=torch.bfloat16) * 0.4)(D, F) * (D ** -0.5)),
            "w_down": _w((lambda *s: torch.randn(*s, dtype=torch.bfloat16) * 0.4)(F, D) * (F ** -0.5)),
        }
    _B_in = _B_setup()

    return {
        "A_x": _A_in["x"],
        "A_k_cache": _A_in["k_cache"],
        "A_v_cache": _A_in["v_cache"],
        "A_wq": _A_in["wq"],
        "A_wo": _A_in["wo"],
        "B_x": _B_in["x"],
        "B_w_gate": _B_in["w_gate"],
        "B_w_up": _B_in["w_up"],
        "B_w_down": _B_in["w_down"],
    }

def reference(A_x, A_k_cache, A_v_cache, A_wq, A_wo, B_x, B_w_gate, B_w_up, B_w_down):
    def _A_ref(x, k_cache, v_cache, wq, wo):
        B, Sq, D = x.shape
        Hq, Dh = 32, 128
        Hkv = k_cache.shape[1]
        rep = Hq // Hkv
        q = (lambda x, *d: x.permute(*d))((x @ wq).reshape(B, Sq, Hq, Dh), 0, 2, 1, 3)
        k = (lambda x, n, axis: torch.repeat_interleave(x, n, dim=axis))(k_cache, rep, axis=1)
        v = (lambda x, n, axis: torch.repeat_interleave(x, n, dim=axis))(v_cache, rep, axis=1)
        scores = torch.einsum("bhqd,bhkd->bhqk", q, k) * (Dh ** -0.5)
        p = _softmax(scores, axis=-1)
        o = torch.einsum("bhqk,bhkd->bhqd", p, v)
        return (lambda x, *d: x.permute(*d))(o, 0, 2, 1, 3).reshape(B, Sq, Hq * Dh) @ wo

    def _B_ref(x, w_gate, w_up, w_down):
        g = torch.einsum("bsd,df->bsf", x, w_gate)
        u = torch.einsum("bsd,df->bsf", x, w_up)
        h = g * u
        return torch.einsum("bsf,fd->bsd", h, w_down)

    x = A_x
    x = x + _A_ref(_layernorm(x, axis=-1), A_k_cache, A_v_cache, A_wq, A_wo)
    x = x + _B_ref(_layernorm(x, axis=-1), B_w_gate, B_w_up, B_w_down)
    x = x + _A_ref(_layernorm(x, axis=-1), A_k_cache, A_v_cache, A_wq, A_wo)
    x = x + _B_ref(_layernorm(x, axis=-1), B_w_gate, B_w_up, B_w_down)
    return x
```

```cpp
#include <cuda_runtime.h>
#include <cuda_bf16.h>
#include <cuda.h>
#include <stdint.h>
#include <string.h>

#define AUXR 88
#define CONR 208
namespace {

constexpr int kH = 32, kSk = 16384, kDh = 128, kD = 512, kF = 1376;
constexpr int kCtas = 128;
constexpr int kThreads = 384;
constexpr int kTile = 4096;
constexpr int kSteps = 128;
constexpr int kGuUnits = 88;

constexpr int SM_RING = 0;
constexpr int SM_RET = 65536;
constexpr int kRetTiles = 39;
constexpr int SM_STAGE = SM_RET + kRetTiles * kTile;
constexpr int kStageStride = 132;
constexpr int SM_Q = SM_STAGE + 8 * kStageStride * 4;
constexpr int SM_XS = SM_Q + 512;
constexpr int SM_BAR = SM_XS + 64;
constexpr int BAR_STAGE = 64, BAR_Q = 65, BAR_TAIL = 67, kNumBars = 68;
constexpr int SM_TOTAL = SM_BAR + kNumBars * 8;
static_assert(SM_TOTAL <= 232448, "smem");

constexpr uint32_t C_B = 1u, C_SWAP = 2u, C_RESET = 4u, C_WAITQ = 8u, C_PUB = 16u, C_PUBO = 1u << 20;
constexpr int C_KREG_SH = 5, C_KSM_SH = 7, C_KSLOT_SH = 8, C_VREG_SH = 11, C_VSM_SH = 13, C_VSLOT_SH = 14;
constexpr uint32_t I_VALID = 0x80u, I_B = 0x40u, I_KEEP = 0x20u;

struct Sched {
  uint2 step[2][kSteps];
  uint32_t initK[2], initV[2];
  uint32_t retGrp[5];
  uint32_t retIsV[5];
  uint32_t flags;
};

struct Params {
  const __nv_bfloat16 *x, *wq, *wo, *wg, *wu, *wd;
  __nv_bfloat16* out;
};

constexpr uint64_t kPolFirst = 0x12F0000000000000ull;
constexpr uint64_t kPolNormal = 0x1000000000000000ull;

__device__ uint64_t g_P[kCtas][kStageStride];
__device__ uint64_t g_Y[kH][kD];
__device__ uint64_t g_X1[kD];
__device__ uint64_t g_GU[kGuUnits][128];
__device__ uint64_t g_Y2[kCtas][kD];
__device__ uint64_t g_X2[2][kD];
__device__ uint64_t g_Q[4][kH][kDh];
__device__ uint32_t g_epoch;

__device__ __forceinline__ uint32_t smem_u32(const void* p) { return (uint32_t)__cvta_generic_to_shared(p); }
__device__ __forceinline__ void mbar_init(uint32_t bar, uint32_t cnt) {
  asm volatile("mbarrier.init.shared::cta.b64 [%0], %1;" ::"r"(bar), "r"(cnt) : "memory");
}
__device__ __forceinline__ void mbar_expect_tx(uint32_t bar, uint32_t bytes) {
  asm volatile("mbarrier.arrive.expect_tx.shared::cta.b64 _, [%0], %1;" ::"r"(bar), "r"(bytes) : "memory");
}
__device__ __forceinline__ void mbar_arrive(uint32_t bar) {
  asm volatile("mbarrier.arrive.shared::cta.b64 _, [%0];" ::"r"(bar) : "memory");
}
constexpr uint32_t kSpinLimit = 1u << 22;
__device__ __forceinline__ void fault() { asm volatile("st.global.u32 [%0], %1;" ::"l"(0ull), "r"(0) : "memory"); }
__device__ __forceinline__ void mbar_wait(uint32_t bar, uint32_t parity) {
  uint32_t ok, it = 0;
#pragma unroll 1
  do {
    asm volatile(
        "{\n.reg .pred p;\nmbarrier.try_wait.parity.shared::cta.b64 p, [%1], %2;\nselp.u32 %0, 1, 0, p;\n}"
        : "=r"(ok) : "r"(bar), "r"(parity) : "memory");
    if (++it > kSpinLimit) { fault(); break; }
  } while (!ok);
}
__device__ __forceinline__ void tma_tile(uint32_t dst, const CUtensorMap* tm, int row, uint32_t bar, uint64_t pol) {
  asm volatile(
      "cp.async.bulk.tensor.3d.shared::cluster.global.mbarrier::complete_tx::bytes.L2::cache_hint "
      "[%0], [%1, {%3, %4, %3}], [%2], %5;" ::"r"(dst), "l"(tm), "r"(bar), "r"(0), "r"(row), "l"(pol)
      : "memory");
}
__device__ __forceinline__ void ldsm4(uint32_t (&r)[4], uint32_t a) {
  asm volatile("ldmatrix.sync.aligned.m8n8.x4.shared.b16 {%0,%1,%2,%3}, [%4];"
               : "=r"(r[0]), "=r"(r[1]), "=r"(r[2]), "=r"(r[3]) : "r"(a));
}
__device__ __forceinline__ void ldsm4t(uint32_t (&r)[4], uint32_t a) {
  asm volatile("ldmatrix.sync.aligned.m8n8.x4.trans.shared.b16 {%0,%1,%2,%3}, [%4];"
               : "=r"(r[0]), "=r"(r[1]), "=r"(r[2]), "=r"(r[3]) : "r"(a));
}
__device__ __forceinline__ void mma16816(float (&c)[4], const uint32_t (&a)[4], uint32_t b0, uint32_t b1) {
  asm volatile(
      "mma.sync.aligned.m16n8k16.row.col.f32.bf16.bf16.f32 {%0,%1,%2,%3}, {%4,%5,%6,%7}, {%8,%9}, {%0,%1,%2,%3};"
      : "+f"(c[0]), "+f"(c[1]), "+f"(c[2]), "+f"(c[3])
      : "r"(a[0]), "r"(a[1]), "r"(a[2]), "r"(a[3]), "r"(b0), "r"(b1));
}
__device__ __forceinline__ uint4 lds128(uint32_t a) {
  uint4 v;
  asm volatile("ld.shared.v4.u32 {%0,%1,%2,%3}, [%4];" : "=r"(v.x), "=r"(v.y), "=r"(v.z), "=r"(v.w) : "r"(a));
  return v;
}
__device__ __forceinline__ float lds32f(uint32_t a) {
  float v;
  asm volatile("ld.shared.f32 %0, [%1];" : "=f"(v) : "r"(a) : "memory");
  return v;
}
__device__ __forceinline__ void sts32f(uint32_t a, float v) {
  asm volatile("st.shared.f32 [%0], %1;" ::"r"(a), "f"(v) : "memory");
}
__device__ __forceinline__ void sts16(uint32_t a, uint16_t v) {
  asm volatile("st.shared.u16 [%0], %1;" ::"r"(a), "h"(v) : "memory");
}
__device__ __forceinline__ uint32_t movm(uint32_t a) {
  uint32_t d;
  asm volatile("movmatrix.sync.aligned.m8n8.trans.b16 %0, %1;" : "=r"(d) : "r"(a));
  return d;
}
__device__ __forceinline__ float ex2(float x) {
  float y;
  asm("ex2.approx.ftz.f32 %0, %1;" : "=f"(y) : "f"(x));
  return y;
}
__device__ __forceinline__ uint32_t pack_bf16x2(float lo, float hi) {
  uint32_t r;
  asm("cvt.rn.bf16x2.f32 %0, %1, %2;" : "=r"(r) : "f"(hi), "f"(lo));
  return r;
}
__device__ __forceinline__ float bf16r(float x) { return __bfloat162float(__float2bfloat16_rn(x)); }
__device__ __forceinline__ float bflo(uint32_t u) { return __uint_as_float(u << 16); }
__device__ __forceinline__ float bfhi(uint32_t u) { return __uint_as_float(u & 0xffff0000u); }
__device__ __forceinline__ void named_bar(int id, int n) { asm volatile("bar.sync %0, %1;" ::"r"(id), "r"(n) : "memory"); }
__device__ __forceinline__ uint4 ldw(const void* p, uint64_t pol) {
  uint4 v;
  asm volatile("ld.global.nc.L1::no_allocate.L2::cache_hint.v4.u32 {%0,%1,%2,%3}, [%4], %5;"
               : "=r"(v.x), "=r"(v.y), "=r"(v.z), "=r"(v.w) : "l"(p), "l"(pol));
  return v;
}
template <int OFF>
__device__ __forceinline__ uint4 ldw_off(const void* p, uint64_t pol) {
  uint4 v;
  asm volatile("ld.global.nc.L1::no_allocate.L2::cache_hint.L2::128B.v4.u32 {%0,%1,%2,%3}, [%4+%6], %5;"
               : "=r"(v.x), "=r"(v.y), "=r"(v.z), "=r"(v.w) : "l"(p), "l"(pol), "n"(OFF));
  return v;
}
template <int OFF>
__device__ __forceinline__ uint32_t ldw4_off(const void* p, uint64_t pol) {
  uint32_t v;
  asm volatile("ld.global.nc.L1::no_allocate.L2::cache_hint.u32 %0, [%1+%3], %2;" : "=r"(v) : "l"(p), "l"(pol), "n"(OFF));
  return v;
}
template <int STRIDE, int N, int J = 0>
__device__ __forceinline__ void ldw_rows(uint4* w, const void* p, uint64_t pol) {
  if constexpr (J < N) {
    w[J] = ldw_off<J * STRIDE>(p, pol);
    ldw_rows<STRIDE, N, J + 1>(w, p, pol);
  }
}
__device__ __forceinline__ uint2 ldw8(const void* p, uint64_t pol) {
  uint2 v;
  asm volatile("ld.global.nc.L1::no_allocate.L2::cache_hint.v2.u32 {%0,%1}, [%2], %3;"
               : "=r"(v.x), "=r"(v.y) : "l"(p), "l"(pol));
  return v;
}
__device__ __forceinline__ unsigned long long gtime() {
  unsigned long long t;
  asm volatile("mov.u64 %0, %globaltimer;" : "=l"(t));
  return t;
}
#define TSTAMP(i) do {} while (0)

__device__ __forceinline__ void ll_store(uint64_t* p, float v, uint32_t tag) {
  uint64_t w = ((uint64_t)tag << 32) | (uint64_t)__float_as_uint(v);
  asm volatile("st.relaxed.gpu.global.b64 [%0], %1;" ::"l"(p), "l"(w) : "memory");
}
__device__ __forceinline__ void ll_store2(uint64_t* p, float v0, float v1, uint32_t tag) {
  uint64_t w0 = ((uint64_t)tag << 32) | (uint64_t)__float_as_uint(v0);
  uint64_t w1 = ((uint64_t)tag << 32) | (uint64_t)__float_as_uint(v1);
  asm volatile("st.relaxed.gpu.global.v2.b64 [%0], {%1, %2};" ::"l"(p), "l"(w0), "l"(w1) : "memory");
}
__device__ __forceinline__ uint64_t ll_raw(const uint64_t* p) {
  uint64_t w;
  asm volatile("ld.relaxed.gpu.global.b64 %0, [%1];" : "=l"(w) : "l"(p) : "memory");
  return w;
}
__device__ __forceinline__ void ll_raw2(const uint64_t* p, uint64_t& w0, uint64_t& w1) {
  asm volatile("ld.relaxed.gpu.global.v2.b64 {%0, %1}, [%2];" : "=l"(w0), "=l"(w1) : "l"(p) : "memory");
}
template <bool SLEEP>
__device__ __forceinline__ bool ll_backoff(uint32_t& it) {
  __nanosleep(SLEEP ? 64 : 20);
  if (++it > kSpinLimit) { fault(); return true; }
  return false;
}
template <bool SLEEP>
__device__ __forceinline__ void ll_pre(const uint64_t* p, uint32_t tag, bool me) {
  if (SLEEP) return;
  if (me) {
    uint32_t it = 0;
#pragma unroll 1
    while ((uint32_t)(ll_raw(p) >> 32) != tag) {
      __nanosleep(SLEEP ? 100 : 20);
      if (++it > kSpinLimit) { fault(); break; }
    }
  }
  __syncwarp();
}
template <int N, bool SLEEP>
__device__ __forceinline__ void ll_load(float (&v)[N], const uint64_t* p, int stride, uint32_t tag) {
  uint32_t it = 0;
  ll_pre<SLEEP>(p, tag, (threadIdx.x & 31) == 31);
#pragma unroll 1
  while (true) {
    uint64_t w[N];
#pragma unroll
    for (int i = 0; i < N; ++i) w[i] = ll_raw(p + i * stride);
    bool ok = true;
#pragma unroll
    for (int i = 0; i < N; ++i) { ok = ok && ((uint32_t)(w[i] >> 32) == tag); v[i] = __uint_as_float((uint32_t)w[i]); }
    if (ok) break;
    if (ll_backoff<SLEEP>(it)) break;
  }
}
template <bool SLEEP>
__device__ __forceinline__ void ll_load4(float (&v)[4], const uint64_t* p, uint32_t tag) {
  uint32_t it = 0;
  ll_pre<SLEEP>(p, tag, (threadIdx.x & 31) == 31);
#pragma unroll 1
  while (true) {
    uint64_t w[4];
    ll_raw2(p, w[0], w[1]);
    ll_raw2(p + 2, w[2], w[3]);
    bool ok = true;
#pragma unroll
    for (int i = 0; i < 4; ++i) { ok = ok && ((uint32_t)(w[i] >> 32) == tag); v[i] = __uint_as_float((uint32_t)w[i]); }
    if (ok) break;
    if (ll_backoff<SLEEP>(it)) break;
  }
}

__device__ __forceinline__ void fma8(float (&acc)[8], const uint4& w, float x) {
  acc[0] = fmaf(bflo(w.x), x, acc[0]); acc[1] = fmaf(bfhi(w.x), x, acc[1]);
  acc[2] = fmaf(bflo(w.y), x, acc[2]); acc[3] = fmaf(bfhi(w.y), x, acc[3]);
  acc[4] = fmaf(bflo(w.z), x, acc[4]); acc[5] = fmaf(bfhi(w.z), x, acc[5]);
  acc[6] = fmaf(bflo(w.w), x, acc[6]); acc[7] = fmaf(bfhi(w.w), x, acc[7]);
}
template <int N>
__device__ __forceinline__ void fold(float* v, int lane, int mask) {
  const bool up = (lane & mask) != 0;
#pragma unroll
  for (int i = 0; i < N / 2; ++i) {
    float send = up ? v[i] : v[i + N / 2];
    float keep = up ? v[i + N / 2] : v[i];
    v[i] = keep + __shfl_xor_sync(0xffffffffu, send, mask);
  }
}
__device__ __forceinline__ float gemv16_fold(float (&acc)[8], int lane) {
  fold<8>(acc, lane, 16);
  fold<4>(acc, lane, 8);
  fold<2>(acc, lane, 4);
  return acc[0];
}
struct W16 { uint4 w[16]; };
template <int STRIDE>
__device__ __forceinline__ void w16_load(W16& w, const char* wp, uint64_t pol) { ldw_rows<STRIDE, 16>(w.w, wp, pol); }
__device__ __forceinline__ float w16_dot(const W16& w, uint32_t xs, int lane) {
  float acc[8];
#pragma unroll
  for (int i = 0; i < 8; ++i) acc[i] = 0.f;
#pragma unroll
  for (int j = 0; j < 16; ++j) fma8(acc, w.w[j], lds32f(xs + j * 4));
  return gemv16_fold(acc, lane);
}
__device__ __forceinline__ int gemv16_col(int lane) {
  return 8 * (lane & 3) + 4 * ((lane >> 4) & 1) + 2 * ((lane >> 3) & 1) + ((lane >> 2) & 1);
}
__device__ __forceinline__ float warp_sum(float v) {
#pragma unroll
  for (int m = 16; m > 0; m >>= 1) v += __shfl_xor_sync(0xffffffffu, v, m);
  return v;
}
__device__ __forceinline__ void layernorm128(const float (&v)[4], uint32_t xn, uint32_t red, int tid, int barid) {
  const int lane = tid & 31, gw = tid >> 5;
  float s = warp_sum((v[0] + v[1]) + (v[2] + v[3]));
  if (lane == 0) sts32f(red + gw * 4, s);
  named_bar(barid, 128);
  const float mean = ((lds32f(red) + lds32f(red + 4)) + (lds32f(red + 8) + lds32f(red + 12))) * (1.0f / kD);
  float q = 0.f;
#pragma unroll
  for (int i = 0; i < 4; ++i) { float d = v[i] - mean; q = fmaf(d, d, q); }
  q = warp_sum(q);
  if (lane == 0) sts32f(red + 16 + gw * 4, q);
  named_bar(barid, 128);
  const float var = ((lds32f(red + 16) + lds32f(red + 20)) + (lds32f(red + 24) + lds32f(red + 28))) * (1.0f / kD);
  const float mb = bf16r(mean);
  const float sd = bf16r(sqrtf(bf16r(bf16r(var) + 1e-5f)));
  const float rs = __frcp_rn(sd);
#pragma unroll
  for (int i = 0; i < 4; ++i) sts32f(xn + (4 * tid + i) * 4, bf16r(bf16r(v[i] - mb) * rs));
  named_bar(barid, 128);
}

__device__ __forceinline__ const char* wo_ptr(const Params& p, int c, int tid) {
  const int lane = tid & 31, gw = tid >> 5;
  return (const char*)(p.wo + (size_t)((c >> 2) * kDh + (lane >> 2) * 16) * kD + (c & 3) * 128 + gw * 32 + (lane & 3) * 8);
}
__device__ __forceinline__ const char* wgu_ptr(const Params& p, int u, int tid) {
  const int lane = tid & 31, gw = tid >> 5;
  const __nv_bfloat16* wsel = (gw >> 1) ? p.wu : p.wg;
  return (const char*)(wsel + (size_t)((u & 3) * 128 + (gw & 1) * 64 + (lane >> 3)) * kF + (u >> 2) * 64 + (lane & 7) * 8);
}
__device__ __forceinline__ int wd_row0(int c) { return c < 96 ? 11 * c : 1056 + 10 * (c - 96); }
template <int J = 0>
__device__ __forceinline__ void wd_load(uint2* w, const char* dp, uint64_t pol) {
  if constexpr (J < 10) {
    w[J].x = ldw4_off<J * kD * 2>(dp, pol);
    w[J].y = ldw4_off<J * kD * 2 + 512>(dp, pol);
    wd_load<J + 1>(w, dp, pol);
  }
}
__device__ __forceinline__ const char* wq_ptr(const Params& p, int c, int tid) {
  const int lane = tid & 31, gw = tid >> 5;
  return (const char*)(p.wq + (size_t)(gw * 128 + (lane >> 2) * 16) * (kH * kDh) + (c >> 2) * kDh + (c & 3) * 32 + (lane & 3) * 8);
}
constexpr uint32_t S_XN = 0, S_OH = 2048, S_RED = 2560, S_HH = 3072, S_ST = 3136;

__device__ __forceinline__ bool tag_ok(uint64_t w, uint32_t tag) { return (uint32_t)(w >> 32) == tag; }
__device__ __forceinline__ float ll_val(uint64_t w) { return __uint_as_float((uint32_t)w); }

__device__ __forceinline__ float glue(const Params& p, int ch, uint32_t tag, int tid, int barid, uint32_t stage,
                                      uint32_t stageStride, uint32_t scr, float xres, W16& w, uint64_t wpol, bool withq) {
  constexpr bool SLEEP = true;
  const int c = blockIdx.x, h = c >> 2, s = c & 3;
  const int lane = tid & 31, gw = tid >> 5;
  const int u = (c + 43 * min(ch, 2)) & 127;
  {
    float M = -INFINITY;
#pragma unroll
    for (int i = 0; i < 8; ++i) M = fmaxf(M, lds32f(stage + i * stageStride + 128 * 4));
    float o = 0.f, L = 0.f;
#pragma unroll
    for (int i = 0; i < 8; ++i) {
      const float e = ex2(lds32f(stage + i * stageStride + 128 * 4) - M);
      o = fmaf(e, lds32f(stage + i * stageStride + tid * 4), o);
      L = fmaf(e, lds32f(stage + i * stageStride + 129 * 4), L);
    }
    ll_store(&g_P[c][tid], o, tag);
    if (tid < 2) ll_store2(&g_P[c][128 + 2 * tid], M, L, tag);
  }
  if (tid == 0 && (ch == 0 || ch == 3)) TSTAMP(40 + (ch == 0 ? 8 : 0));
  {
    const uint64_t* pp = &g_P[4 * h][0];
    const uint64_t* pml = pp + ((lane >> 1) & 3) * kStageStride + 128 + (lane & 1);
    uint64_t w0, w1, w2, w3, wm;
    uint32_t it = 0;
    ll_pre<SLEEP>(pp + (lane & 3) * kStageStride + tid, tag, lane >= 28);
#pragma unroll 1
    while (true) {
      w0 = ll_raw(pp + tid); w1 = ll_raw(pp + kStageStride + tid);
      w2 = ll_raw(pp + 2 * kStageStride + tid); w3 = ll_raw(pp + 3 * kStageStride + tid);
      wm = ll_raw(pml);
      if (tag_ok(w0, tag) && tag_ok(w1, tag) && tag_ok(w2, tag) && tag_ok(w3, tag) && tag_ok(wm, tag)) break;
      if (ll_backoff<SLEEP>(it)) break;
    }
    __syncwarp();
    const float ml = ll_val(wm);
    float M = fmaxf(ml, __shfl_xor_sync(0xffffffffu, ml, 2));
    M = fmaxf(M, __shfl_xor_sync(0xffffffffu, M, 4));
    M = __shfl_sync(0xffffffffu, M, 0);
    const float e0 = ex2(__shfl_sync(0xffffffffu, ml, 0) - M), e1 = ex2(__shfl_sync(0xffffffffu, ml, 2) - M);
    const float e2 = ex2(__shfl_sync(0xffffffffu, ml, 4) - M), e3 = ex2(__shfl_sync(0xffffffffu, ml, 6) - M);
    const float L = (e0 * __shfl_sync(0xffffffffu, ml, 1) + e1 * __shfl_sync(0xffffffffu, ml, 3)) +
                    (e2 * __shfl_sync(0xffffffffu, ml, 5) + e3 * __shfl_sync(0xffffffffu, ml, 7));
    const float o = (e0 * ll_val(w0) + e1 * ll_val(w1)) + (e2 * ll_val(w2) + e3 * ll_val(w3));
    named_bar(barid, 128);
    sts32f(scr + S_OH + tid * 4, bf16r(o * __frcp_rn(L)));
    named_bar(barid, 128);
    if (tid == 0 && (ch == 0 || ch == 3)) TSTAMP(41 + (ch == 0 ? 8 : 0));
    const float y = w16_dot(w, scr + S_OH + (lane >> 2) * 64, lane);
    ll_store(&g_Y[h][s * 128 + gw * 32 + gemv16_col(lane)], y, tag);
  }
  const bool guLane = (u >> 2) * 64 + (lane & 7) * 8 < kF;
  if (u < kGuUnits && guLane) {
    w16_load<4 * kF * 2>(w, wgu_ptr(p, u, tid), wpol);
  } else {
#pragma unroll
    for (int j = 0; j < 16; ++j) w.w[j] = make_uint4(0, 0, 0, 0);
  }
  if (tid == 0 && (ch == 0 || ch == 3)) TSTAMP(42 + (ch == 0 ? 8 : 0));
  float x1own;
  {
    float v[1];
    ll_load<1, SLEEP>(v, &g_Y[tid >> 2][4 * c + (tid & 3)], 0, tag);
    float t = v[0];
    t += __shfl_xor_sync(0xffffffffu, t, 4);
    t += __shfl_xor_sync(0xffffffffu, t, 8);
    t += __shfl_xor_sync(0xffffffffu, t, 16);
    if (lane < 4) sts32f(scr + S_RED + (gw * 4 + lane) * 4, t);
    named_bar(barid, 128);
    const int j = tid & 3;
    const float a = (lds32f(scr + S_RED + j * 4) + lds32f(scr + S_RED + (4 + j) * 4)) +
                    (lds32f(scr + S_RED + (8 + j) * 4) + lds32f(scr + S_RED + (12 + j) * 4));
    x1own = bf16r(xres + bf16r(a));
    if (tid < 4) ll_store(&g_X1[4 * c + tid], x1own, tag);
  }
  if (tid == 0 && (ch == 0 || ch == 3)) TSTAMP(43 + (ch == 0 ? 8 : 0));
  if (u < kGuUnits) {
    float v[4];
    ll_load4<SLEEP>(v, &g_X1[4 * tid], tag);
    if (tid == 0 && (ch == 0 || ch == 3)) TSTAMP(44 + (ch == 0 ? 8 : 0));
    layernorm128(v, scr + S_XN, scr + S_ST, tid, barid);
    float acc[8];
#pragma unroll
    for (int i = 0; i < 8; ++i) acc[i] = 0.f;
    const uint32_t xs = scr + S_XN + ((u & 3) * 128 + (gw & 1) * 64 + (lane >> 3)) * 4;
#pragma unroll
    for (int j = 0; j < 16; ++j) fma8(acc, w.w[j], lds32f(xs + j * 16));
    fold<8>(acc, lane, 16);
    fold<4>(acc, lane, 8);
    const uint32_t r = scr + S_OH + (gw * 64 + (lane & 7) * 8 + ((lane >> 4) & 1) * 4 + ((lane >> 3) & 1) * 2) * 4;
    sts32f(r, acc[0]);
    sts32f(r + 4, acc[1]);
  }
  const int f0 = wd_row0(c), nrow = c < 96 ? 11 : 10;
  uint2 wd[11];
  {
    const char* dp = (const char*)(p.wd + (size_t)f0 * kD + 2 * tid);
    wd_load(wd, dp, wpol);
    wd[10] = make_uint2(0, 0);
    if (nrow == 11) { wd[10].x = ldw4_off<10 * kD * 2>(dp, wpol); wd[10].y = ldw4_off<10 * kD * 2 + 512>(dp, wpol); }
  }
  if (u < kGuUnits) {
    named_bar(barid, 128);
    const uint32_t r = scr + S_OH + ((tid >> 6) * 128 + (tid & 63)) * 4;
    ll_store(&g_GU[u][tid], lds32f(r) + lds32f(r + 256), tag);
  }
  if (tid == 0 && ch == 0) TSTAMP(59);
  {
    const int f = f0 + (tid >> 3), part = tid & 7;
    float v[1] = {0.f};
    const bool on = tid < 8 * nrow;
    const uint64_t* gp = &g_GU[(f >> 6) * 4 + (part & 3)][(part >> 2) * 64 + (f & 63)];
    uint32_t it = 0;
#pragma unroll 1
    while (on) {
      const uint64_t wv = ll_raw(gp);
      v[0] = ll_val(wv);
      if (tag_ok(wv, tag)) break;
      if (ll_backoff<SLEEP>(it)) break;
    }
    __syncwarp();
    float t = v[0];
    t += __shfl_xor_sync(0xffffffffu, t, 1);
    t += __shfl_xor_sync(0xffffffffu, t, 2);
    t = bf16r(t);
    const float hv = bf16r(t * __shfl_xor_sync(0xffffffffu, t, 4));
    if (part == 0 && tid < 88) sts32f(scr + S_HH + (tid >> 3) * 4, on ? hv : 0.f);
    named_bar(barid, 128);
    if (tid == 0 && ch == 0) TSTAMP(60);
    float a0 = 0.f, a1 = 0.f, a2 = 0.f, a3 = 0.f;
#pragma unroll
    for (int j = 0; j < 11; ++j) {
      const float hj = lds32f(scr + S_HH + j * 4);
      a0 = fmaf(bflo(wd[j].x), hj, a0); a1 = fmaf(bfhi(wd[j].x), hj, a1);
      a2 = fmaf(bflo(wd[j].y), hj, a2); a3 = fmaf(bfhi(wd[j].y), hj, a3);
    }
    ll_store2(&g_Y2[c][2 * tid], a0, a1, tag);
    ll_store2(&g_Y2[c][256 + 2 * tid], a2, a3, tag);
  }
  if (withq) {
    w16_load<kH * kDh * 2>(w, wq_ptr(p, c, tid), kPolFirst);
  } else {
#pragma unroll
    for (int j = 0; j < 16; ++j) w.w[j] = make_uint4(0, 0, 0, 0);
  }
  if (tid == 0 && (ch == 0 || ch == 3)) TSTAMP(45 + (ch == 0 ? 8 : 0));
  {
    const int r0 = tid >> 2, j = tid & 3;
    const uint64_t* pp = &g_Y2[r0][4 * c + j];
    float t;
    uint32_t it = 0;
#pragma unroll 1
    while (true) {
      const uint64_t w0 = ll_raw(pp), w1 = ll_raw(pp + 32 * kD), w2 = ll_raw(pp + 64 * kD), w3 = ll_raw(pp + 96 * kD);
      t = (ll_val(w0) + ll_val(w1)) + (ll_val(w2) + ll_val(w3));
      if (tag_ok(w0, tag) && tag_ok(w1, tag) && tag_ok(w2, tag) && tag_ok(w3, tag)) break;
      if (ll_backoff<SLEEP>(it)) break;
    }
    __syncwarp();
    t += __shfl_xor_sync(0xffffffffu, t, 4);
    t += __shfl_xor_sync(0xffffffffu, t, 8);
    t += __shfl_xor_sync(0xffffffffu, t, 16);
    named_bar(barid, 128);
    if (lane < 4) sts32f(scr + S_RED + (gw * 4 + lane) * 4, t);
    named_bar(barid, 128);
    const float a = (lds32f(scr + S_RED + j * 4) + lds32f(scr + S_RED + (4 + j) * 4)) +
                    (lds32f(scr + S_RED + (8 + j) * 4) + lds32f(scr + S_RED + (12 + j) * 4));
    return bf16r(x1own + bf16r(a));
  }
}

template <bool SLEEP>
__device__ __forceinline__ void qproj(int b, uint64_t* qx, const float (&v)[4], uint32_t tag, int tid, int barid,
                                      uint32_t scr, uint32_t smemBase, const W16& wq) {
  constexpr bool EARLY = !SLEEP;
  const int c = blockIdx.x, s = c & 3;
  const int lane = tid & 31, gw = tid >> 5;
  layernorm128(v, scr + S_XN, scr + S_ST, tid, barid);
  if (tid == 0 && b == 0) TSTAMP(EARLY ? 4 : 61);
  const uint32_t xs = scr + S_XN + (gw * 128 + (lane >> 2) * 16) * 4;
  const float y = w16_dot(wq, xs, lane);
  sts32f(scr + S_RED + (gw * 32 + gemv16_col(lane)) * 4, y);
  named_bar(barid, 128);
  if (tid < 32) {
    const uint32_t r = scr + S_RED + tid * 4;
    const float qv = (lds32f(r) + lds32f(r + 128)) + (lds32f(r + 256) + lds32f(r + 384));
    ll_store(qx + s * 32 + tid, bf16r(qv), tag);
  }
  if (tid == 0 && b == 0) TSTAMP(EARLY ? 5 : 62);
  float q1[1];
  ll_load<1, SLEEP>(q1, qx + tid, 0, tag);
  const int d = tid, kk = d >> 4, r = d & 15;
  const uint32_t off = (kk >> 1) * 64 + ((r & 7) >> 1) * 16 + (kk & 1) * 8 + (r >> 3) * 4 + (r & 1) * 2;
  sts16(smemBase + SM_Q + b * 256 + off, (uint16_t)(__float_as_uint(q1[0]) >> 16));
}

struct Acc { float o[4]; float m, l; };

__device__ __forceinline__ void qk_smem(float (&sa)[4], float (&sb)[4], uint32_t ka, uint32_t qa) {
#pragma unroll
  for (int kp = 0; kp < 4; ++kp) {
    const uint4 qf = lds128(qa + kp * 64);
    uint32_t a[4], a2[4];
    ldsm4(a, (ka ^ (((2 * kp) & 3) << 5)) + (kp >> 1) * 2048);
    ldsm4(a2, (ka ^ (((2 * kp + 1) & 3) << 5)) + (kp >> 1) * 2048);
    mma16816(sa, a, qf.x, qf.y);
    mma16816(sb, a2, qf.z, qf.w);
  }
}
__device__ __forceinline__ void k_load(uint32_t (&r)[8][4], uint32_t ka) {
#pragma unroll
  for (int kk = 0; kk < 8; ++kk) ldsm4(r[kk], (ka ^ ((kk & 3) << 5)) + (kk >> 2) * 2048);
}
__device__ __forceinline__ void qk_reg(float (&sa)[4], float (&sb)[4], const uint32_t (&r)[8][4], uint32_t qa) {
#pragma unroll
  for (int kp = 0; kp < 4; ++kp) {
    const uint4 qf = lds128(qa + kp * 64);
    mma16816(sa, r[2 * kp], qf.x, qf.y);
    mma16816(sb, r[2 * kp + 1], qf.z, qf.w);
  }
}
__device__ __forceinline__ void pv_smem(float (&o)[4], uint32_t va, uint32_t b0, uint32_t b1, int g) {
#pragma unroll
  for (int m = 0; m < 8; ++m) {
    uint32_t a[4];
    ldsm4t(a, (va ^ ((m & 3) << 5)) + (m >> 2) * 2048);
    mma16816(o, a, g == m ? b0 : 0u, g == m ? b1 : 0u);
  }
}
__device__ __forceinline__ void v_load(uint32_t (&r)[8][4], uint32_t va) {
#pragma unroll
  for (int m = 0; m < 8; ++m) ldsm4t(r[m], (va ^ ((m & 3) << 5)) + (m >> 2) * 2048);
}
__device__ __forceinline__ void pv_reg(float (&o)[4], const uint32_t (&r)[8][4], uint32_t b0, uint32_t b1, int g) {
#pragma unroll
  for (int m = 0; m < 8; ++m) mma16816(o, r[m], g == m ? b0 : 0u, g == m ? b1 : 0u);
}
__device__ __forceinline__ void write_partial(const Acc& a, uint32_t dst, int lane) {
  const int g = lane >> 2, t = lane & 3;
  float l = a.l;
  l += __shfl_xor_sync(0xffffffffu, l, 4);
  l += __shfl_xor_sync(0xffffffffu, l, 8);
  l += __shfl_xor_sync(0xffffffffu, l, 16);
  sts32f(dst + (32 * t + g) * 4, a.o[0]);
  sts32f(dst + (32 * t + 16 + g) * 4, a.o[1]);
  sts32f(dst + (32 * t + 8 + g) * 4, a.o[2]);
  sts32f(dst + (32 * t + 24 + g) * 4, a.o[3]);
  if (lane == 0) { sts32f(dst + 128 * 4, a.m); sts32f(dst + 129 * 4, l); }
}

template <int AUXREG, int CONREG>
__global__ void __launch_bounds__(kThreads, 1)
fused_kernel(const __grid_constant__ CUtensorMap tmK, const __grid_constant__ CUtensorMap tmV,
             const __grid_constant__ Params p, const __grid_constant__ Sched sc) {
  extern __shared__ __align__(1024) uint8_t smem_raw[];
  const uint32_t sm = smem_u32(smem_raw);
  const int warp = threadIdx.x >> 5, lane = threadIdx.x & 31;
  const int c = blockIdx.x;
  uint32_t tag;
  asm volatile("ld.relaxed.gpu.global.u32 %0, [%1];" : "=r"(tag) : "l"(&g_epoch) : "memory");
  tag += 1;
  if (threadIdx.x == 256) {
    for (int i = 0; i < 64; ++i) mbar_init(sm + SM_BAR + i * 8, 1);
    mbar_init(sm + SM_BAR + BAR_STAGE * 8, 8);
    mbar_init(sm + SM_BAR + BAR_Q * 8, 1);
    mbar_init(sm + SM_BAR + (BAR_Q + 1) * 8, 1);
    mbar_init(sm + SM_BAR + BAR_TAIL * 8, 8);
    asm volatile("fence.mbarrier_init.release.cluster;" ::: "memory");
    asm volatile("fence.proxy.async;" ::: "memory");
  }
  __syncthreads();

  if (warp >= 8) {
    asm volatile("setmaxnreg.dec.sync.aligned.u32 %0;" ::"n"(AUXREG));
#pragma unroll 1
    for (int ch = 0; ch < 4; ++ch) {
      int tid = threadIdx.x - 256;
      asm volatile("" : "+r"(tid));
      const int b = ch & 1;
      const bool fin = ch >= 2;
      const uint64_t wpol = (ch == 2) ? kPolNormal : kPolFirst;
      W16 w;
      if (ch == 0) __nanosleep(10000);
      if (ch != 2) w16_load<kD * 2>(w, wo_ptr(p, c, tid), wpol);
      const float xres = fin ? lds32f(sm + SM_XS + (b * 4 + (tid & 3)) * 4) : __bfloat162float(p.x[b * kD + 4 * c + (tid & 3)]);
      mbar_wait(sm + SM_BAR + (ch == 3 ? BAR_TAIL : BAR_STAGE) * 8, ch == 3 ? 0 : b);
      if (ch == 2) w16_load<kD * 2>(w, wo_ptr(p, c, tid), wpol);
      if (tid == 0) TSTAMP(ch == 0 ? 16 : ch == 1 ? 18 : ch == 2 ? 20 : 2);
      const float x2 = glue(p, ch, tag * 4 + ch, tid, 3, ch == 3 ? sm + SM_RING : sm + SM_STAGE, ch == 3 ? 8192 : kStageStride * 4,
                            sm + SM_STAGE, xres, w, wpol, !fin);
      if (fin) {
        if (tid < 4) p.out[b * kD + 4 * c + tid] = __float2bfloat16_rn(x2);
      } else {
        if (tid < 4) {
          ll_store(&g_X2[b][4 * c + tid], x2, tag);
          sts32f(sm + SM_XS + (b * 4 + tid) * 4, x2);
        }
        float v[4];
        if (tid == 0 && b == 0) TSTAMP(54);
        ll_load4<true>(v, &g_X2[b][4 * tid], tag);
        if (tid == 0 && b == 0) TSTAMP(55);
        qproj<true>(b, &g_Q[2 + b][c >> 2][0], v, tag, tid, 3, sm + SM_STAGE, sm, w);
        named_bar(3, 128);
        if (tid == 0) mbar_arrive(sm + SM_BAR + (BAR_Q + b) * 8);
      }
      if (tid == 0) TSTAMP(ch == 0 ? 17 : ch == 1 ? 19 : ch == 2 ? 21 : 3);
    }
    if (c == 0 && threadIdx.x == 256) g_epoch = tag;
  } else {
    asm volatile("setmaxnreg.inc.sync.aligned.u32 %0;" ::"n"(CONREG));
    const int h = c >> 2;
    const int tb = (warp == 7) ? 1 : 0;
    const uint32_t ringK = sm + SM_RING + warp * 8192, ringV = ringK + 4096;
    const uint32_t ret0 = sm + SM_RET + warp * 5 * kTile;
    const uint32_t bar0 = sm + SM_BAR + warp * 64;
    const int rowBase = c * 4096 + warp * 16;
    if (threadIdx.x == 0) TSTAMP(0);

    {
      const int b = warp >> 2, tid = threadIdx.x & 127;
      W16 wq;
      const uint2 xr = ldw8(p.x + b * kD + 4 * tid, kPolNormal);
      w16_load<kH * kDh * 2>(wq, wq_ptr(p, c, tid), kPolFirst);
      if (lane == 0) {
        const uint32_t ik = sc.initK[tb], iv = sc.initV[tb];
        mbar_expect_tx(bar0, kTile);
        tma_tile(ringK, &tmK, rowBase + (ik & 31) * 128, bar0, (ik & I_KEEP) ? kPolNormal : kPolFirst);
        mbar_expect_tx(bar0 + 8, kTile);
        tma_tile(ringV, &tmV, rowBase + (iv & 31) * 128, bar0 + 8, (iv & I_KEEP) ? kPolNormal : kPolFirst);
      }
      __syncwarp();
      const float v[4] = {bflo(xr.x), bfhi(xr.x), bflo(xr.y), bfhi(xr.y)};
      qproj<false>(b, &g_Q[b][h][0], v, tag, tid, 4 + b, b ? sm + SM_RET : sm + SM_STAGE, sm, wq);
      asm volatile("fence.proxy.async.shared::cta;" ::: "memory");
      named_bar(1, 256);
      if (lane == 0) {
        const int nret = (warp == 7) ? 4 : 5;
        for (int i = 0; i < nret; ++i) {
          mbar_expect_tx(bar0 + 16 + i * 8, kTile);
          tma_tile(ret0 + i * kTile, sc.retIsV[i] ? &tmV : &tmK, rowBase + sc.retGrp[i] * 128, bar0 + 16 + i * 8, kPolFirst);
        }
      }
      __syncwarp();
    }
    if (threadIdx.x == 0) TSTAMP(1);

    const int g = lane >> 2, t = lane & 3, mi = lane >> 3, l7 = lane & 7;
    const uint32_t offK = (l7 + 8 * (mi & 1)) * 128 + (((mi >> 1) ^ l7) << 4);
    const uint32_t offV = (l7 + 8 * (mi >> 1)) * 128 + (((mi & 1) ^ l7) << 4);
    const uint32_t qa0 = sm + SM_Q + t * 16;
    constexpr float kScale = 0.08838834764831845f * 1.4426950408889634f;
    uint32_t kr0[8][4], kr1[8][4], kr2[8][4], vr0[8][4], vr1[8][4];
#pragma unroll
    for (int i = 0; i < 8; ++i)
#pragma unroll
      for (int j = 0; j < 4; ++j) { kr0[i][j] = 0; kr1[i][j] = 0; kr2[i][j] = 0; vr0[i][j] = 0; vr1[i][j] = 0; }
    Acc cur, oth;
#pragma unroll
    for (int i = 0; i < 4; ++i) { cur.o[i] = 0.f; oth.o[i] = 0.f; }
    cur.m = -INFINITY; cur.l = 0.f; oth.m = -INFINITY; oth.l = 0.f;
    uint32_t kph = 0, vph = 0;

#pragma unroll 1
    for (int st = 0; st < kSteps; ++st) {
      const uint2 d = sc.step[tb][st];
      const uint32_t ctl = d.x;
      const uint32_t b = ctl & C_B;
      if (ctl & C_SWAP) { Acc tmp = cur; cur = oth; oth = tmp; }
      if (ctl & C_RESET) {
        cur.o[0] = cur.o[1] = cur.o[2] = cur.o[3] = 0.f;
        cur.m = -INFINITY; cur.l = 0.f;
      }
      if (ctl & C_WAITQ) {
        mbar_wait(sm + SM_BAR + (BAR_Q + b) * 8, 0);
      }
      const uint32_t qa = qa0 + b * 256;
      float sa[4] = {0.f, 0.f, 0.f, 0.f}, sb[4] = {0.f, 0.f, 0.f, 0.f};
      {
        const uint32_t kreg = (ctl >> C_KREG_SH) & 3, kslot = (ctl >> C_KSLOT_SH) & 7;
        const bool ksm = (ctl >> C_KSM_SH) & 1;
        const uint32_t kaddr = kslot ? ret0 + (kslot - 1) * kTile : ringK;
        const uint32_t kbar = kslot ? bar0 + 8 + kslot * 8 : bar0;
        if (ksm) {
          mbar_wait(kbar, kslot ? b : kph);
          if (!kslot) kph ^= 1;
        }
        const uint32_t ka = kaddr + offK;
        if (kreg == 0) {
          qk_smem(sa, sb, ka, qa);
        } else if (kreg == 1) {
          if (ksm) k_load(kr0, ka);
          qk_reg(sa, sb, kr0, qa);
        } else if (kreg == 2) {
          if (ksm) k_load(kr1, ka);
          qk_reg(sa, sb, kr1, qa);
        } else {
          if (ksm) k_load(kr2, ka);
          qk_reg(sa, sb, kr2, qa);
        }
        const uint32_t ik = d.y & 0xff;
        if (ik & I_VALID) {
          __syncwarp();
          if (lane == 0) {
            mbar_expect_tx(kbar, kTile);
            tma_tile(kaddr, &tmK, rowBase + ((ik & I_B) ? kH * kSk : 0) + (ik & 31) * 128, kbar,
                     (ik & I_KEEP) ? kPolNormal : kPolFirst);
          }
        }
      }
      const float t0 = (sa[0] + sb[0]) * kScale, t1 = (sa[2] + sb[2]) * kScale;
      float mx = fmaxf(t0, t1);
      mx = fmaxf(mx, __shfl_xor_sync(0xffffffffu, mx, 4));
      mx = fmaxf(mx, __shfl_xor_sync(0xffffffffu, mx, 8));
      mx = fmaxf(mx, __shfl_xor_sync(0xffffffffu, mx, 16));
      if (mx > cur.m) {
        const float f = ex2(cur.m - mx);
        cur.l *= f;
        cur.o[0] *= f; cur.o[1] *= f; cur.o[2] *= f; cur.o[3] *= f;
        cur.m = mx;
      }
      const float p0 = ex2(t0 - cur.m), p1 = ex2(t1 - cur.m);
      cur.l += p0 + p1;
      const uint32_t b0 = movm(pack_bf16x2(p0, p0)), b1 = movm(pack_bf16x2(p1, p1));
      {
        const uint32_t vreg = (ctl >> C_VREG_SH) & 3, vslot = (ctl >> C_VSLOT_SH) & 7;
        const bool vsm = (ctl >> C_VSM_SH) & 1;
        const uint32_t vaddr = vslot ? ret0 + (vslot - 1) * kTile : ringV;
        const uint32_t vbar = vslot ? bar0 + 8 + vslot * 8 : bar0 + 8;
        if (vsm) {
          mbar_wait(vbar, vslot ? b : vph);
          if (!vslot) vph ^= 1;
        }
        const uint32_t va = vaddr + offV;
        if (vreg == 0) {
          pv_smem(cur.o, va, b0, b1, g);
        } else if (vreg == 1) {
          if (vsm) v_load(vr0, va);
          pv_reg(cur.o, vr0, b0, b1, g);
        } else {
          if (vsm) v_load(vr1, va);
          pv_reg(cur.o, vr1, b0, b1, g);
        }
        const uint32_t iv = (d.y >> 8) & 0xff;
        if (iv & I_VALID) {
          __syncwarp();
          if (lane == 0) {
            mbar_expect_tx(vbar, kTile);
            tma_tile(vaddr, &tmV, rowBase + ((iv & I_B) ? kH * kSk : 0) + (iv & 31) * 128, vbar,
                     (iv & I_KEEP) ? kPolNormal : kPolFirst);
          }
        }
      }
      if (ctl & (C_PUB | C_PUBO)) {
        Acc pub;
        const bool po = ctl & C_PUBO;
        pub.o[0] = po ? oth.o[0] : cur.o[0]; pub.o[1] = po ? oth.o[1] : cur.o[1];
        pub.o[2] = po ? oth.o[2] : cur.o[2]; pub.o[3] = po ? oth.o[3] : cur.o[3];
        pub.m = po ? oth.m : cur.m; pub.l = po ? oth.l : cur.l;
        write_partial(pub, sm + SM_STAGE + warp * kStageStride * 4, lane);
        __syncwarp();
        if (lane == 0) mbar_arrive(sm + SM_BAR + BAR_STAGE * 8);
      }
    }

    write_partial(cur, ringK, lane);
    __syncwarp();
    if (lane == 0) mbar_arrive(sm + SM_BAR + BAR_TAIL * 8);
  }
}

struct SchedCfg { int nL2, coverA, coverB, spread, preLead, flags; };

enum Place { P_RING = 0, P_SM, P_REG };
struct StepSpec { int b, pass, grp, kplace, kidx, vplace, vidx; uint32_t flags; };

void build_sched(Sched& sc, const SchedCfg& cfg) {
  memset(&sc, 0, sizeof(sc));
  sc.flags = cfg.flags;
  const int G_R0 = 27, G_R1 = 28, G_MIX = 29, G_S0 = 30, G_S1 = 31;
  const int nS = 27 - cfg.nL2;
  sc.retGrp[0] = G_S0; sc.retIsV[0] = 0; sc.retGrp[1] = G_S0; sc.retIsV[1] = 1;
  sc.retGrp[2] = G_S1; sc.retIsV[2] = 0; sc.retGrp[3] = G_S1; sc.retIsV[3] = 1;
  sc.retGrp[4] = G_MIX; sc.retIsV[4] = 1;
  for (int tb = 0; tb < 2; ++tb) {
    StepSpec sp[kSteps];
    int n = 0;
    auto add = [&](int b, int pass, int grp, uint32_t flags) {
      StepSpec s; s.b = b; s.pass = pass; s.grp = grp; s.flags = flags;
      s.kplace = P_RING; s.kidx = 0; s.vplace = P_RING; s.vidx = 0;
      if (grp == G_R0) { s.kplace = P_REG; s.kidx = 1; s.vplace = P_REG; s.vidx = 1; }
      if (grp == G_R1) { s.kplace = P_REG; s.kidx = 2; s.vplace = P_REG; s.vidx = 2; }
      if (grp == G_MIX) { s.kplace = P_REG; s.kidx = 3; if (tb == 0) { s.vplace = P_SM; s.vidx = 5; } }
      if (grp == G_S0) { s.kplace = P_SM; s.kidx = 1; s.vplace = P_SM; s.vidx = 2; }
      if (grp == G_S1) { s.kplace = P_SM; s.kidx = 3; s.vplace = P_SM; s.vidx = 4; }
      sp[n++] = s;
    };
    auto passB = [&](int b, int nStream, uint32_t first) {
      int kept[16], nk = 0;
      kept[nk++] = G_S0;
      for (int i = 0; i < cfg.nL2; ++i) {
        kept[nk++] = nS + i;
        if (i == 0) kept[nk++] = G_S1;
        if (i == 1) kept[nk++] = G_MIX;
      }
      if (cfg.nL2 < 1) kept[nk++] = G_S1;
      if (cfg.nL2 < 2) kept[nk++] = G_MIX;
      kept[nk++] = G_R0; kept[nk++] = G_R1;
      int is = 0, ik = 0;
      while (is < nStream || ik < nk) {
        for (int k = 0; k < cfg.spread && is < nStream; ++k) { add(b, 1, is++, first); first = 0; }
        if (ik < nk) { add(b, 1, kept[ik++], first); first = 0; }
      }
    };
    for (int g = 0; g < 27; ++g) {
      add(0, 0, g, 0);
      if (g == 1) add(0, 0, G_S0, 0);
      if (g == 3) add(0, 0, G_S1, 0);
    }
    add(0, 0, G_R0, 0); add(0, 0, G_R1, 0); add(0, 0, G_MIX, C_PUB);
    for (int g = 0; g < cfg.coverA; ++g) add(1, 0, g, g == 0 ? (C_SWAP | C_RESET) : 0);
    passB(0, nS - cfg.coverB, C_SWAP | C_RESET | C_WAITQ);
    {
      uint32_t first = C_SWAP;
      for (int g = cfg.coverA; g < 27; ++g) {
        add(1, 0, g, first); first = 0;
        if (g == 26 - 4) add(1, 0, G_S0, 0);
        if (g == 26 - 2) add(1, 0, G_S1, 0);
      }
      add(1, 0, G_R0, 0); add(1, 0, G_R1, 0); add(1, 0, G_MIX, C_PUB);
    }
    for (int g = nS - cfg.coverB; g < nS; ++g) add(0, 1, g, g == nS - cfg.coverB ? C_SWAP : 0);
    passB(1, nS, C_SWAP | C_RESET | C_WAITQ);
    sp[n - 1 - cfg.preLead].flags |= C_PUBO;
    auto desc = [&](const StepSpec& s) -> uint32_t {
      const bool keep = s.pass == 0 && s.grp >= nS && s.grp < 27;
      return I_VALID | (s.b ? I_B : 0) | (keep ? I_KEEP : 0) | (uint32_t)s.grp;
    };
    auto viaRingK = [&](const StepSpec& s) { return s.kplace == P_RING || (s.kplace == P_REG && s.pass == 0); };
    auto viaRingV = [&](const StepSpec& s) { return s.vplace == P_RING || (s.vplace == P_REG && s.pass == 0); };
    for (int i = 0; i < n; ++i) {
      const StepSpec& s = sp[i];
      uint32_t ctl = s.flags | (s.b ? C_B : 0), iss = 0;
      if (s.kplace == P_REG) ctl |= s.kidx << C_KREG_SH;
      if (s.kplace == P_SM) ctl |= (s.kidx << C_KSLOT_SH) | (1u << C_KSM_SH);
      if (viaRingK(s)) {
        ctl |= 1u << C_KSM_SH;
        for (int j = i + 1; j < n; ++j) if (viaRingK(sp[j])) { iss |= desc(sp[j]); break; }
      } else if (s.kplace == P_SM && s.pass == 1 && s.b == 0) {
        iss |= I_VALID | I_B | (uint32_t)s.grp;
      }
      if (s.vplace == P_REG) ctl |= s.vidx << C_VREG_SH;
      if (s.vplace == P_SM) ctl |= (s.vidx << C_VSLOT_SH) | (1u << C_VSM_SH);
      if (viaRingV(s)) {
        ctl |= 1u << C_VSM_SH;
        for (int j = i + 1; j < n; ++j) if (viaRingV(sp[j])) { iss |= desc(sp[j]) << 8; break; }
      } else if (s.vplace == P_SM && s.pass == 1 && s.b == 0) {
        iss |= (I_VALID | I_B | (uint32_t)s.grp) << 8;
      }
      sc.step[tb][i] = make_uint2(ctl, iss);
    }
    for (int j = 0; j < n; ++j) if (viaRingK(sp[j])) { sc.initK[tb] = desc(sp[j]); break; }
    for (int j = 0; j < n; ++j) if (viaRingV(sp[j])) { sc.initV[tb] = desc(sp[j]); break; }
  }
}

typedef CUresult (*EncodeTiledFn)(CUtensorMap*, CUtensorMapDataType, cuuint32_t, void*, const cuuint64_t*,
                                  const cuuint64_t*, const cuuint32_t*, const cuuint32_t*, CUtensorMapInterleave,
                                  CUtensorMapSwizzle, CUtensorMapL2promotion, CUtensorMapFloatOOBfill);

void make_map(CUtensorMap* tm, EncodeTiledFn enc, void* base) {
  cuuint64_t dims[3] = {64, (cuuint64_t)2 * kH * kSk, 2};
  cuuint64_t strides[2] = {256, 128};
  cuuint32_t box[3] = {64, 16, 2};
  cuuint32_t es[3] = {1, 1, 1};
  enc(tm, CU_TENSOR_MAP_DATA_TYPE_BFLOAT16, 3, base, dims, strides, box, es, CU_TENSOR_MAP_INTERLEAVE_NONE,
      CU_TENSOR_MAP_SWIZZLE_128B, CU_TENSOR_MAP_L2_PROMOTION_NONE, CU_TENSOR_MAP_FLOAT_OOB_FILL_NONE);
}

SchedCfg g_cfg = {4, 17, 17, 1, 12, 0};

}

extern "C" void kernel_launch(void* const* d_in, const int* in_sizes, int n_in, void* d_out, int out_size) {
  (void)in_sizes; (void)n_in; (void)out_size;
  static EncodeTiledFn enc = nullptr;
  auto kern = fused_kernel<AUXR, CONR>;
  if (!enc) {
    cudaDriverEntryPointQueryResult qr;
    cudaGetDriverEntryPoint("cuTensorMapEncodeTiled", (void**)&enc, cudaEnableDefault, &qr);
    cudaFuncSetAttribute(kern, cudaFuncAttributeMaxDynamicSharedMemorySize, SM_TOTAL);
  }
  CUtensorMap tmK, tmV;
  make_map(&tmK, enc, d_in[1]);
  make_map(&tmV, enc, d_in[2]);
  Sched sc;
  build_sched(sc, g_cfg);
  Params p;
  p.x = (const __nv_bfloat16*)d_in[0];
  p.wq = (const __nv_bfloat16*)d_in[3];
  p.wo = (const __nv_bfloat16*)d_in[4];
  p.wg = (const __nv_bfloat16*)d_in[6];
  p.wu = (const __nv_bfloat16*)d_in[7];
  p.wd = (const __nv_bfloat16*)d_in[8];
  p.out = (__nv_bfloat16*)d_out;
  kern<<<kCtas, kThreads, SM_TOTAL, cudaStreamPerThread>>>(tmK, tmV, p, sc);
}
```

```cpp
#include <cuda_runtime.h>
#include <cuda_bf16.h>
#include <cuda.h>
#include <stdint.h>

namespace {

constexpr int kH = 32, kSk = 16384, kDh = 128, kD = 512, kF = 1376;
constexpr int kCtas = 128;
constexpr int kThreads = 384;
constexpr int kTile = 4096;
constexpr int kSteps = 128;
constexpr int kGuUnits = 88;
constexpr int kDnUnits = 43;

constexpr int SM_RING = 0;
constexpr int SM_RET = 65536;
constexpr int kRetTiles = 39;
constexpr int SM_Q = SM_RET + kRetTiles * kTile;
constexpr int SM_XS = SM_Q + 512;
constexpr int SM_BAR = SM_XS + 64;
constexpr int BAR_STAGE = 64, BAR_Q = 65, BAR_TAIL = 67, BAR_PRE = 68, kNumBars = 70;
constexpr int SM_STAGE = SM_BAR + kNumBars * 8;
constexpr int kStageStride = 132;
constexpr int SM_TOTAL = SM_STAGE + 8 * kStageStride * 4;
static_assert(SM_TOTAL <= 232448 && SM_STAGE % 16 == 0, "smem");

constexpr uint32_t C_B = 1u, C_SWAP = 2u, C_RESET = 4u, C_WAITQ = 8u, C_PUB = 16u, C_PUBO = 1u << 20;
constexpr uint32_t C_CLAIM0 = 1u << 21, C_DYN = 1u << 22;
constexpr uint32_t C_PREW = 1u << 25;
constexpr int C_POOL_SH = 23;
constexpr int C_KREG_SH = 5, C_KSM_SH = 7, C_KSLOT_SH = 8, C_VREG_SH = 11, C_VSM_SH = 13, C_VSLOT_SH = 14;
constexpr uint32_t I_VALID = 0x80u, I_B = 0x40u, I_KEEP = 0x20u;

__device__ constexpr int kRetGrp[5] = {30, 30, 31, 31, 29};
__device__ constexpr bool kRetIsV[5] = {false, true, false, true, true};
constexpr int kEarlyRet0 = 3;

struct alignas(8) Step { uint32_t x, y; };
struct Sched {
  Step step[2][kSteps];
  uint32_t nSteps;
  uint32_t poolGrp[3], poolSize[3];
};

struct SchedCfg {
  int nL2;
  int coverA, coverB;
  int preLead;
  int lag;
  int dyn, dynA;
  int prewLead;
};

enum Place { P_RING = 0, P_SM, P_REG };
struct StepSpec { int b, pass, grp, kplace, kidx, vplace, vidx; uint32_t flags; };

constexpr Sched build_sched(const SchedCfg& cfg) {
  Sched sc{};
  const int G_R0 = 27, G_R1 = 28, G_MIX = 29, G_S0 = 30, G_S1 = 31;
  const int nS = 27 - cfg.nL2;
  for (int tb = 0; tb < 2; ++tb) {
    StepSpec sp[kSteps] = {};
    int n = 0;
    auto add = [&](int b, int pass, int grp, uint32_t flags) {
      StepSpec s{}; s.b = b; s.pass = pass; s.grp = grp; s.flags = flags;
      s.kplace = P_RING; s.kidx = 0; s.vplace = P_RING; s.vidx = 0;
      if (grp == G_R0) { s.kplace = P_REG; s.kidx = 1; s.vplace = P_REG; s.vidx = 1; }
      if (grp == G_R1) { s.kplace = P_REG; s.kidx = 2; s.vplace = P_REG; s.vidx = 2; }
      if (grp == G_MIX) { s.kplace = P_REG; s.kidx = 3; if (tb == 0) { s.vplace = P_SM; s.vidx = 5; } }
      if (grp == G_S0) { s.kplace = P_SM; s.kidx = 1; s.vplace = P_SM; s.vidx = 2; }
      if (grp == G_S1) { s.kplace = P_SM; s.kidx = 3; s.vplace = P_SM; s.vidx = 4; }
      sp[n++] = s;
    };
    int kept[32] = {}, nk = 0;
    {
      const int onsm[5] = {G_S0, G_S1, G_MIX, G_R0, G_R1};
      for (int i = 0; i < 5 || i < cfg.nL2; ++i) {
        if (i < 5) kept[nk++] = onsm[i];
        if (i < cfg.nL2) kept[nk++] = nS + i;
      }
    }
    int cur = 0;
    bool fresh[2][2] = {{false, true}, {true, true}};
    auto step = [&](int b, int pass, int grp, uint32_t flags) {
      if (b != cur) { flags |= C_SWAP; cur = b; }
      if (fresh[pass][b]) { flags |= C_RESET | (pass ? C_WAITQ : 0); fresh[pass][b] = false; }
      add(b, pass, grp, flags);
    };
    auto endPass = [&](int b, int pass, int pool, int g0, int cnt, uint32_t flags) {
      sp[n - 1].flags |= C_CLAIM0 | ((uint32_t)pool << C_POOL_SH);
      step(b, pass, g0, flags | C_DYN | ((uint32_t)pool << C_POOL_SH));
      sc.poolGrp[pool] = g0 + 1;
      sc.poolSize[pool] = 32 * cnt;
    };
    const int dA = cfg.dynA, dB = cfg.dyn;
    for (int g = 0; g < 27; ++g) {
      if (g >= nS - dA && g < nS) continue;
      step(0, 0, g, 0);
      if (g == 1) step(0, 0, G_S0, 0);
      if (g == 3) step(0, 0, G_S1, 0);
    }
    step(0, 0, G_R0, 0); step(0, 0, G_R1, 0); step(0, 0, G_MIX, 0);
    endPass(0, 0, 0, nS - dA, dA - 1, C_PUB);
    for (int g = 0; g < cfg.coverA; ++g) step(1, 0, g, 0);
    {
      int is0 = 0, ig1 = cfg.coverA, ik = 0;
      const int n0 = nS - cfg.coverB;
      auto skip = [&] { while (ig1 >= nS - dA && ig1 < nS) ++ig1; };
      skip();
      while (ik < nk || is0 < n0) {
        if (ik < nk) step(0, 1, kept[ik++], 0);
        if (is0 < n0) step(0, 1, is0++, 0);
        else if (ig1 < 27 && (ig1 < nS || ik >= 2 * (ig1 - nS) + cfg.lag)) { step(1, 0, ig1++, 0); skip(); }
      }
      while (ig1 < 27) { step(1, 0, ig1++, 0); skip(); }
      step(1, 0, G_S0, 0); step(1, 0, G_S1, 0);
      step(1, 0, G_R0, 0); step(1, 0, G_R1, 0); step(1, 0, G_MIX, 0);
      endPass(1, 0, 1, nS - dA, dA - 1, C_PUB);
    }
    for (int g = nS - cfg.coverB; g < nS; ++g) step(0, 1, g, 0);
    {
      int is = 0, ik = 0;
      while (is < nS - dB || ik < nk) {
        if (is < nS - dB) step(1, 1, is++, 0);
        if (ik < nk) step(1, 1, kept[ik++], 0);
      }
      endPass(1, 1, 2, nS - dB, dB - 1, 0);
      sc.nSteps = n;
    }
    sp[n - 1 - cfg.preLead].flags |= C_PUBO;
    for (int i = 0; i < n; ++i)
      if (sp[i].flags & (C_PUB | C_PUBO)) sp[i - cfg.prewLead].flags |= C_PREW;
    auto desc = [&](const StepSpec& s) -> uint32_t {
      const bool keep = s.pass == 0 && s.grp >= nS && s.grp < 27;
      return I_VALID | (s.b ? I_B : 0) | (keep ? I_KEEP : 0) | (uint32_t)s.grp;
    };
    auto viaRingK = [&](const StepSpec& s) { return s.kplace == P_RING || (s.kplace == P_REG && s.pass == 0); };
    auto viaRingV = [&](const StepSpec& s) { return s.vplace == P_RING || (s.vplace == P_REG && s.pass == 0); };
    for (int i = 0; i < n; ++i) {
      const StepSpec& s = sp[i];
      uint32_t ctl = s.flags | (s.b ? C_B : 0), iss = 0;
      if (s.kplace == P_REG) ctl |= s.kidx << C_KREG_SH;
      if (s.kplace == P_SM) ctl |= (s.kidx << C_KSLOT_SH) | (1u << C_KSM_SH);
      if (viaRingK(s)) {
        ctl |= 1u << C_KSM_SH;
        for (int j = i + 1; j < n; ++j) if (viaRingK(sp[j])) { iss |= desc(sp[j]); break; }
      } else if (s.kplace == P_SM && s.pass == 1 && s.b == 0) {
        iss |= I_VALID | I_B | (uint32_t)s.grp;
      }
      if (s.vplace == P_REG) ctl |= s.vidx << C_VREG_SH;
      if (s.vplace == P_SM) ctl |= (s.vidx << C_VSLOT_SH) | (1u << C_VSM_SH);
      if (viaRingV(s)) {
        ctl |= 1u << C_VSM_SH;
        for (int j = i + 1; j < n; ++j) if (viaRingV(sp[j])) { iss |= desc(sp[j]) << 8; break; }
      } else if (s.vplace == P_SM && s.pass == 1 && s.b == 0) {
        iss |= (I_VALID | I_B | (uint32_t)s.grp) << 8;
      }
      sc.step[tb][i].x = ctl;
      sc.step[tb][i].y = iss;
    }
  }
  return sc;
}

constexpr SchedCfg kCfg = {6, 15, 16, 12, 2, 6, 3, 4};
constexpr Sched kSched = build_sched(kCfg);
__constant__ Sched c_sched = kSched;

struct Params {
  const __nv_bfloat16 *x, *k, *v, *wq, *wo, *wg, *wu, *wd;
  __nv_bfloat16* out;
};

constexpr uint64_t kPolFirst = 0x12F0000000000000ull;
constexpr uint64_t kPolNormal = 0x1000000000000000ull;

constexpr int kPStride = 68;
__device__ __align__(128) uint64_t g_P[kCtas][kPStride];
__device__ __align__(128) uint64_t g_Y[kH][kD / 2];
__device__ __align__(128) uint64_t g_X1[kD];
__device__ __align__(128) uint64_t g_GU[kGuUnits][64];
__device__ __align__(128) uint64_t g_Y2[kDnUnits][kD / 2];
__device__ __align__(128) uint64_t g_X2[2][kD];
__device__ __align__(128) uint64_t g_QP[kCtas][128];
__device__ __align__(128) uint32_t g_claim[3][kH];
__device__ uint32_t g_epoch;

__device__ __forceinline__ uint32_t smem_u32(const void* p) { return (uint32_t)__cvta_generic_to_shared(p); }
__device__ __forceinline__ void mbar_init(uint32_t bar, uint32_t cnt) {
  asm volatile("mbarrier.init.shared::cta.b64 [%0], %1;" ::"r"(bar), "r"(cnt) : "memory");
}
__device__ __forceinline__ void mbar_expect_tx(uint32_t bar, uint32_t bytes) {
  asm volatile("mbarrier.arrive.expect_tx.shared::cta.b64 _, [%0], %1;" ::"r"(bar), "r"(bytes) : "memory");
}
__device__ __forceinline__ void mbar_arrive(uint32_t bar) {
  asm volatile("mbarrier.arrive.shared::cta.b64 _, [%0];" ::"r"(bar) : "memory");
}
constexpr uint32_t kSpinLimit = 1u << 22;
__device__ __forceinline__ void fault() { asm volatile("st.global.u32 [%0], %1;" ::"l"(0ull), "r"(0) : "memory"); }
__device__ __forceinline__ void mbar_wait(uint32_t bar, uint32_t parity) {
  uint32_t ok, it = 0;
#pragma unroll 1
  do {
    asm volatile(
        "{\n.reg .pred p;\nmbarrier.try_wait.parity.shared::cta.b64 p, [%1], %2;\nselp.u32 %0, 1, 0, p;\n}"
        : "=r"(ok) : "r"(bar), "r"(parity) : "memory");
    if (++it > kSpinLimit) { fault(); break; }
  } while (!ok);
}
__device__ __forceinline__ void tma_tile(uint32_t dst, const CUtensorMap* tm, int row, uint32_t bar, uint64_t pol) {
  asm volatile(
      "cp.async.bulk.tensor.3d.shared::cluster.global.mbarrier::complete_tx::bytes.L2::cache_hint "
      "[%0], [%1, {%3, %4, %3}], [%2], %5;" ::"r"(dst), "l"(tm), "r"(bar), "r"(0), "r"(row), "l"(pol)
      : "memory");
}
__device__ __forceinline__ void l2_keep_tile(const void* gptr) {
  asm volatile("cp.async.bulk.prefetch.L2.global [%0], %1;" ::"l"(gptr), "r"(kTile) : "memory");
}
__device__ __forceinline__ void ldsm4(uint32_t (&r)[4], uint32_t a) {
  asm volatile("ldmatrix.sync.aligned.m8n8.x4.shared.b16 {%0,%1,%2,%3}, [%4];"
               : "=r"(r[0]), "=r"(r[1]), "=r"(r[2]), "=r"(r[3]) : "r"(a));
}
__device__ __forceinline__ void ldsm4t(uint32_t (&r)[4], uint32_t a) {
  asm volatile("ldmatrix.sync.aligned.m8n8.x4.trans.shared.b16 {%0,%1,%2,%3}, [%4];"
               : "=r"(r[0]), "=r"(r[1]), "=r"(r[2]), "=r"(r[3]) : "r"(a));
}
__device__ __forceinline__ void mma16816(float (&c)[4], const uint32_t (&a)[4], uint32_t b0, uint32_t b1) {
  asm volatile(
      "mma.sync.aligned.m16n8k16.row.col.f32.bf16.bf16.f32 {%0,%1,%2,%3}, {%4,%5,%6,%7}, {%8,%9}, {%0,%1,%2,%3};"
      : "+f"(c[0]), "+f"(c[1]), "+f"(c[2]), "+f"(c[3])
      : "r"(a[0]), "r"(a[1]), "r"(a[2]), "r"(a[3]), "r"(b0), "r"(b1));
}
__device__ __forceinline__ uint4 lds128(uint32_t a) {
  uint4 v;
  asm volatile("ld.shared.v4.u32 {%0,%1,%2,%3}, [%4];" : "=r"(v.x), "=r"(v.y), "=r"(v.z), "=r"(v.w) : "r"(a));
  return v;
}
__device__ __forceinline__ float lds32f(uint32_t a) {
  float v;
  asm volatile("ld.shared.f32 %0, [%1];" : "=f"(v) : "r"(a) : "memory");
  return v;
}
__device__ __forceinline__ void sts32f(uint32_t a, float v) {
  asm volatile("st.shared.f32 [%0], %1;" ::"r"(a), "f"(v) : "memory");
}
__device__ __forceinline__ void sts16(uint32_t a, uint16_t v) {
  asm volatile("st.shared.u16 [%0], %1;" ::"r"(a), "h"(v) : "memory");
}
__device__ __forceinline__ uint32_t movm(uint32_t a) {
  uint32_t d;
  asm volatile("movmatrix.sync.aligned.m8n8.trans.b16 %0, %1;" : "=r"(d) : "r"(a));
  return d;
}
__device__ __forceinline__ float ex2(float x) {
  float y;
  asm("ex2.approx.ftz.f32 %0, %1;" : "=f"(y) : "f"(x));
  return y;
}
__device__ __forceinline__ uint32_t pack_bf16x2(float lo, float hi) {
  uint32_t r;
  asm("cvt.rn.bf16x2.f32 %0, %1, %2;" : "=r"(r) : "f"(hi), "f"(lo));
  return r;
}
__device__ __forceinline__ float bf16r(float x) { return __bfloat162float(__float2bfloat16_rn(x)); }
__device__ __forceinline__ float bflo(uint32_t u) { return __uint_as_float(u << 16); }
__device__ __forceinline__ float bfhi(uint32_t u) { return __uint_as_float(u & 0xffff0000u); }
__device__ __forceinline__ void named_bar(int id, int n) { asm volatile("bar.sync %0, %1;" ::"r"(id), "r"(n) : "memory"); }
__device__ __forceinline__ uint4 ldw(const void* p, uint64_t pol) {
  uint4 v;
  asm volatile("ld.global.nc.L1::no_allocate.L2::cache_hint.v4.u32 {%0,%1,%2,%3}, [%4], %5;"
               : "=r"(v.x), "=r"(v.y), "=r"(v.z), "=r"(v.w) : "l"(p), "l"(pol));
  return v;
}
template <int OFF>
__device__ __forceinline__ uint4 ldw_off(const void* p, uint64_t pol) {
  uint4 v;
  asm volatile("ld.global.nc.L1::no_allocate.L2::cache_hint.L2::128B.v4.u32 {%0,%1,%2,%3}, [%4+%6], %5;"
               : "=r"(v.x), "=r"(v.y), "=r"(v.z), "=r"(v.w) : "l"(p), "l"(pol), "n"(OFF));
  return v;
}
template <int STRIDE, int N, int J = 0>
__device__ __forceinline__ void ldw_rows(uint4* w, const void* p, uint64_t pol) {
  if constexpr (J < N) {
    w[J] = ldw_off<J * STRIDE>(p, pol);
    ldw_rows<STRIDE, N, J + 1>(w, p, pol);
  }
}

__device__ __forceinline__ void ll_store(uint64_t* p, float v, uint32_t tag) {
  uint64_t w = ((uint64_t)tag << 32) | (uint64_t)__float_as_uint(v);
  asm volatile("st.relaxed.gpu.global.b64 [%0], %1;" ::"l"(p), "l"(w) : "memory");
}
__device__ __forceinline__ void ll_store2(uint64_t* p, float v0, float v1, uint32_t tag) {
  uint64_t w0 = ((uint64_t)tag << 32) | (uint64_t)__float_as_uint(v0);
  uint64_t w1 = ((uint64_t)tag << 32) | (uint64_t)__float_as_uint(v1);
  asm volatile("st.relaxed.gpu.global.v2.b64 [%0], {%1, %2};" ::"l"(p), "l"(w0), "l"(w1) : "memory");
}
__device__ __forceinline__ uint64_t ll_raw(const uint64_t* p) {
  uint64_t w;
  asm volatile("ld.relaxed.gpu.global.b64 %0, [%1];" : "=l"(w) : "l"(p) : "memory");
  return w;
}
__device__ __forceinline__ void ll_raw2(const uint64_t* p, uint64_t& w0, uint64_t& w1) {
  asm volatile("ld.relaxed.gpu.global.v2.b64 {%0, %1}, [%2];" : "=l"(w0), "=l"(w1) : "l"(p) : "memory");
}
__device__ __forceinline__ bool tag_ok(uint64_t w, uint32_t tag) { return (uint32_t)(w >> 32) == tag; }
__device__ __forceinline__ float ll_val(uint64_t w) { return __uint_as_float((uint32_t)w); }
__device__ __forceinline__ uint64_t pair_pack(float a, float b, uint32_t tag) {
  const uint32_t ua = __float_as_uint(a) + 0x80u, ub = __float_as_uint(b) + 0x80u;
  return ((uint64_t)((ua & 0xffffff00u) | (ub >> 24)) << 32) | (((ub << 8) & 0xffff0000u) | tag);
}
__device__ __forceinline__ bool pair_ok(uint64_t w, uint32_t tag) { return ((uint32_t)w & 0xffffu) == tag; }
__device__ __forceinline__ float pair_a(uint64_t w) { return __uint_as_float((uint32_t)(w >> 32) & 0xffffff00u); }
__device__ __forceinline__ float pair_b(uint64_t w) { return __uint_as_float(((uint32_t)(w >> 32) << 24) | (((uint32_t)w >> 16) << 8)); }
__device__ __forceinline__ float pair_val(uint64_t w, int odd) { return odd ? pair_b(w) : pair_a(w); }
__device__ __forceinline__ void st_word(uint64_t* p, uint64_t w) {
  asm volatile("st.relaxed.gpu.global.b64 [%0], %1;" ::"l"(p), "l"(w) : "memory");
}
__device__ __forceinline__ void st_word2(uint64_t* p, uint64_t w0, uint64_t w1) {
  asm volatile("st.relaxed.gpu.global.v2.b64 [%0], {%1, %2};" ::"l"(p), "l"(w0), "l"(w1) : "memory");
}
__device__ __forceinline__ void pair_publish(uint64_t* row, int t, float v, uint32_t tag) {
  const float o = __shfl_xor_sync(0xffffffffu, v, 1);
  if (!(t & 1)) st_word(row + (t >> 1), pair_pack(v, o, tag));
}
__device__ __forceinline__ uint32_t make_tag(uint32_t epoch, uint32_t k) { return (epoch * 8 + k) % 65535u + 1u; }
__device__ __forceinline__ bool ll_backoff(uint32_t& it, uint32_t slp) {
  if (slp) __nanosleep(slp);
  if (++it > kSpinLimit) { fault(); return true; }
  return false;
}
__device__ __forceinline__ uint64_t pair_load(const uint64_t* p, uint32_t tag, uint32_t slp) {
  uint32_t it = 0;
  uint64_t w;
#pragma unroll 1
  while (true) {
    w = ll_raw(p);
    if (pair_ok(w, tag)) break;
    if (ll_backoff(it, slp)) break;
  }
  return w;
}
__device__ __forceinline__ void pair_load4(uint64_t (&w)[4], const uint64_t* p, int stride, uint32_t tag, uint32_t slp) {
  uint32_t it = 0;
#pragma unroll 1
  while (true) {
    w[0] = ll_raw(p); w[1] = ll_raw(p + stride); w[2] = ll_raw(p + 2 * stride); w[3] = ll_raw(p + 3 * stride);
    if (pair_ok(w[0], tag) && pair_ok(w[1], tag) && pair_ok(w[2], tag) && pair_ok(w[3], tag)) break;
    if (ll_backoff(it, slp)) break;
  }
}
__device__ __forceinline__ void ll_load4(float (&v)[4], const uint64_t* p, uint32_t tag, uint32_t slp) {
  uint32_t it = 0;
  uint64_t w0, w1, w2, w3;
#pragma unroll 1
  while (true) {
    ll_raw2(p, w0, w1);
    ll_raw2(p + 2, w2, w3);
    if (tag_ok(w0, tag) && tag_ok(w1, tag) && tag_ok(w2, tag) && tag_ok(w3, tag)) break;
    if (ll_backoff(it, slp)) break;
  }
  v[0] = ll_val(w0); v[1] = ll_val(w1); v[2] = ll_val(w2); v[3] = ll_val(w3);
}

__device__ __forceinline__ void fma8(float (&acc)[8], const uint4& w, float x) {
  acc[0] = fmaf(bflo(w.x), x, acc[0]); acc[1] = fmaf(bfhi(w.x), x, acc[1]);
  acc[2] = fmaf(bflo(w.y), x, acc[2]); acc[3] = fmaf(bfhi(w.y), x, acc[3]);
  acc[4] = fmaf(bflo(w.z), x, acc[4]); acc[5] = fmaf(bfhi(w.z), x, acc[5]);
  acc[6] = fmaf(bflo(w.w), x, acc[6]); acc[7] = fmaf(bfhi(w.w), x, acc[7]);
}
template <int N>
__device__ __forceinline__ void fold(float* v, int lane, int mask) {
  const bool up = (lane & mask) != 0;
#pragma unroll
  for (int i = 0; i < N / 2; ++i) {
    float send = up ? v[i] : v[i + N / 2];
    float keep = up ? v[i + N / 2] : v[i];
    v[i] = keep + __shfl_xor_sync(0xffffffffu, send, mask);
  }
}
struct W16 { uint4 w[16]; };
template <int STRIDE>
__device__ __forceinline__ void w16_load(W16& w, const char* wp, uint64_t pol) { ldw_rows<STRIDE, 16>(w.w, wp, pol); }
__device__ __forceinline__ float warp_sum(float v) {
#pragma unroll
  for (int m = 16; m > 0; m >>= 1) v += __shfl_xor_sync(0xffffffffu, v, m);
  return v;
}
__device__ __forceinline__ void layernorm128(const float (&v)[4], uint32_t xn, uint32_t red, int tid, int barid) {
  const int lane = tid & 31, gw = tid >> 5;
  const float mw = warp_sum((v[0] + v[1]) + (v[2] + v[3])) * (1.0f / 128);
  float q = 0.f;
#pragma unroll
  for (int i = 0; i < 4; ++i) { float d = v[i] - mw; q = fmaf(d, d, q); }
  q = warp_sum(q);
  if (lane == 0) { sts32f(red + gw * 4, mw); sts32f(red + 16 + gw * 4, q); }
  named_bar(barid, 128);
  const float m0 = lds32f(red), m1 = lds32f(red + 4), m2 = lds32f(red + 8), m3 = lds32f(red + 12);
  const float mean = ((m0 + m1) + (m2 + m3)) * 0.25f;
  const float dm = ((m0 - mean) * (m0 - mean) + (m1 - mean) * (m1 - mean)) + ((m2 - mean) * (m2 - mean) + (m3 - mean) * (m3 - mean));
  const float var = (((lds32f(red + 16) + lds32f(red + 20)) + (lds32f(red + 24) + lds32f(red + 28))) + 128.f * dm) * (1.0f / kD);
  const float mb = bf16r(mean);
  const float sd = bf16r(sqrtf(bf16r(bf16r(var) + 1e-5f)));
  const float rs = __frcp_rn(sd);
#pragma unroll
  for (int i = 0; i < 4; ++i) sts32f(xn + (4 * tid + i) * 4, bf16r(bf16r(v[i] - mb) * rs));
  named_bar(barid, 128);
}

__device__ __forceinline__ int unit_row(int tid) { return ((tid >> 5) & 1) * 64 + ((tid & 31) >> 3); }
__device__ __forceinline__ const char* wo_ptr(const Params& p, int c, int tid) {
  return (const char*)(p.wo + (size_t)((c >> 2) * kDh + unit_row(tid)) * kD + (c & 3) * 128 + (tid >> 6) * 64 + (tid & 7) * 8);
}
__device__ __forceinline__ const char* wgu_ptr(const Params& p, int u, int tid) {
  const __nv_bfloat16* wsel = (tid >> 6) ? p.wu : p.wg;
  return (const char*)(wsel + (size_t)((u & 3) * 128 + unit_row(tid)) * kF + (u >> 2) * 64 + (tid & 7) * 8);
}
__device__ __forceinline__ const char* wq_ptr(const Params& p, int c, int tid) {
  return (const char*)(p.wq + (size_t)((c & 3) * 128 + unit_row(tid)) * (kH * kDh) + (c >> 2) * kDh + (tid >> 6) * 64 + (tid & 7) * 8);
}
__device__ __forceinline__ int dn_unit(int u) { return u >= kGuUnits ? u - kGuUnits : u == 29 ? 40 : u == 58 ? 41 : u == 87 ? 42 : -1; }
__device__ __forceinline__ const char* wd_ptr(const Params& p, int v, int tid) {
  return (const char*)(p.wd + (size_t)(32 * v + 16 * (tid >> 6)) * kD + (tid & 63) * 8);
}
constexpr uint32_t S_XN = 0, S_UR = 2048, S_ST = 3136, S_RED = 3200, S_HH = 4096;

__device__ __forceinline__ void glue(const Params& p, int ch, uint32_t tag, int tid0, uint32_t sm, uint32_t stage,
                                     uint32_t stageStride, float xres, W16& w, uint64_t wpol) {
  constexpr int barid = 3;
  const uint32_t scr = sm + SM_STAGE;
  const uint32_t slp = ch == 3 ? 0 : 64;
  const int c = blockIdx.x, h = c >> 2, s = c & 3, b = ch & 1;
  const int u = (c + 43 * min(ch, 2)) & 127;
  const int dv = dn_unit(u);
  const int nIt = ch < 2 ? 3 : 2;
  float xown = xres;
#pragma unroll 1
  for (int it = 0; it < nIt; ++it) {
    int tid = tid0;
    asm volatile("" : "+r"(tid));
    const int lane = tid & 31, gw = tid >> 5;
    const bool active = it != 1 || u < kGuUnits;
    if (it == 0) {
      {
        float M = -INFINITY;
#pragma unroll
        for (int i = 0; i < 8; ++i) M = fmaxf(M, lds32f(stage + i * stageStride + 128 * 4));
        float o = 0.f, L = 0.f;
#pragma unroll
        for (int i = 0; i < 8; ++i) {
          const float e = ex2(lds32f(stage + i * stageStride + 128 * 4) - M);
          o = fmaf(e, lds32f(stage + i * stageStride + tid * 4), o);
          L = fmaf(e, lds32f(stage + i * stageStride + 129 * 4), L);
        }
        pair_publish(&g_P[c][0], tid, o, tag);
        if (tid < 2) ll_store2(&g_P[c][64 + 2 * tid], M, L, tag);
      }
      const uint64_t* pp = &g_P[4 * h][tid >> 1];
      const uint64_t* pml = &g_P[4 * h + (lane & 3)][64];
      uint64_t w0, w1, w2, w3, wm, wl;
      uint32_t spin = 0;
#pragma unroll 1
      while (true) {
        w0 = ll_raw(pp); w1 = ll_raw(pp + kPStride); w2 = ll_raw(pp + 2 * kPStride); w3 = ll_raw(pp + 3 * kPStride);
        ll_raw2(pml, wm, wl);
        if (pair_ok(w0, tag) && pair_ok(w1, tag) && pair_ok(w2, tag) && pair_ok(w3, tag) && tag_ok(wm, tag) && tag_ok(wl, tag)) break;
        if (ll_backoff(spin, slp)) break;
      }
      __syncwarp();
      float M = fmaxf(ll_val(wm), __shfl_xor_sync(0xffffffffu, ll_val(wm), 1));
      M = fmaxf(M, __shfl_xor_sync(0xffffffffu, M, 2));
      const float e = ex2(ll_val(wm) - M);
      float L = e * ll_val(wl);
      const float e0 = __shfl_sync(0xffffffffu, e, 0), e1 = __shfl_sync(0xffffffffu, e, 1);
      const float e2 = __shfl_sync(0xffffffffu, e, 2), e3 = __shfl_sync(0xffffffffu, e, 3);
      L += __shfl_xor_sync(0xffffffffu, L, 1);
      L += __shfl_xor_sync(0xffffffffu, L, 2);
      const int odd = tid & 1;
      const float o = (e0 * pair_val(w0, odd) + e1 * pair_val(w1, odd)) + (e2 * pair_val(w2, odd) + e3 * pair_val(w3, odd));
      if (ch < 2 && tid < 64) st_word(&g_QP[c][b * 64 + tid], 0);
      if (stage == scr) named_bar(barid, 128);
      sts32f(scr + S_XN + tid * 4, bf16r(o * __frcp_rn(L)));
      named_bar(barid, 128);
    } else if (active) {
      float v[4];
      ll_load4(v, (it == 1 ? &g_X1[0] : &g_X2[b][0]) + 4 * tid, tag, slp);
      layernorm128(v, scr + S_XN, scr + S_ST, tid, barid);
    }
    if (active) {
      float acc[8];
#pragma unroll
      for (int i = 0; i < 8; ++i) acc[i] = 0.f;
      const int blk = it == 0 ? 0 : it == 1 ? (u & 3) : s;
      const uint32_t xs = scr + S_XN + (blk * 128 + unit_row(tid)) * 4;
#pragma unroll
      for (int j = 0; j < 16; ++j) fma8(acc, w.w[j], lds32f(xs + j * 16));
      fold<8>(acc, lane, 16);
      fold<4>(acc, lane, 8);
      const uint32_t r = scr + S_UR + (gw * 64 + (lane & 7) * 8 + ((lane >> 4) & 1) * 4 + ((lane >> 3) & 1) * 2) * 4;
      sts32f(r, acc[0]);
      sts32f(r + 4, acc[1]);
      named_bar(barid, 128);
      const uint32_t q = scr + S_UR + ((tid >> 6) * 128 + (tid & 63)) * 4;
      const float y = lds32f(q) + lds32f(q + 256);
      pair_publish(it == 0 ? &g_Y[h][s * 64] : it == 1 ? &g_GU[u][0] : &g_QP[c][b * 64], tid, y, tag);
    }
    auto load_gu = [&] {
      if (u >= kGuUnits) {
        w16_load<kD * 2>(w, wd_ptr(p, dv, tid), wpol);
      } else if ((u >> 2) * 64 + (lane & 7) * 8 < kF) {
        w16_load<4 * kF * 2>(w, wgu_ptr(p, u, tid), wpol);
      } else {
#pragma unroll
        for (int j = 0; j < 16; ++j) w.w[j] = make_uint4(0, 0, 0, 0);
      }
    };
    auto load_wq = [&] {
      if (ch < 2) {
        w16_load<4 * kH * kDh * 2>(w, wq_ptr(p, c, tid), kPolFirst);
      } else {
#pragma unroll
        for (int j = 0; j < 16; ++j) w.w[j] = make_uint4(0, 0, 0, 0);
      }
    };
    if (it == 0) {
      float t = pair_val(pair_load(&g_Y[tid >> 2][2 * c + ((tid >> 1) & 1)], tag, slp), tid & 1);
      t += __shfl_xor_sync(0xffffffffu, t, 4);
      t += __shfl_xor_sync(0xffffffffu, t, 8);
      t += __shfl_xor_sync(0xffffffffu, t, 16);
      if (lane < 4) sts32f(scr + S_RED + (gw * 4 + lane) * 4, t);
      named_bar(barid, 128);
      const int j = tid & 3;
      const float a = (lds32f(scr + S_RED + j * 4) + lds32f(scr + S_RED + (4 + j) * 4)) +
                      (lds32f(scr + S_RED + (8 + j) * 4) + lds32f(scr + S_RED + (12 + j) * 4));
      xown = bf16r(xown + bf16r(a));
      if (tid < 4) ll_store(&g_X1[4 * c + tid], xown, tag);
      load_gu();
    } else if (it == 1) {
      if (dv >= 0) {
        if (u < kGuUnits) w16_load<kD * 2>(w, wd_ptr(p, dv, tid), wpol);
        const int f = 32 * dv + 2 * (tid >> 3), part = tid & 7;
        const uint64_t wv = pair_load(&g_GU[(f >> 6) * 4 + (part & 3)][(part >> 2) * 32 + ((f & 63) >> 1)], tag, slp);
        __syncwarp();
        float t0 = pair_a(wv), t1 = pair_b(wv);
        t0 += __shfl_xor_sync(0xffffffffu, t0, 1); t1 += __shfl_xor_sync(0xffffffffu, t1, 1);
        t0 += __shfl_xor_sync(0xffffffffu, t0, 2); t1 += __shfl_xor_sync(0xffffffffu, t1, 2);
        t0 = bf16r(t0); t1 = bf16r(t1);
        const float h0 = bf16r(t0 * __shfl_xor_sync(0xffffffffu, t0, 4)), h1 = bf16r(t1 * __shfl_xor_sync(0xffffffffu, t1, 4));
        if (part == 0) { sts32f(scr + S_HH + (tid >> 3) * 8, h0); sts32f(scr + S_HH + (tid >> 3) * 8 + 4, h1); }
        named_bar(barid, 128);
        float acc[8];
#pragma unroll
        for (int i = 0; i < 8; ++i) acc[i] = 0.f;
#pragma unroll
        for (int j = 0; j < 16; ++j) fma8(acc, w.w[j], lds32f(scr + S_HH + ((tid >> 6) * 16 + j) * 4));
        const uint32_t dn = scr + (tid >> 6) * 2048 + (tid & 63) * 32;
        asm volatile("st.shared.v4.f32 [%0], {%1,%2,%3,%4};" ::"r"(dn), "f"(acc[0]), "f"(acc[1]), "f"(acc[2]), "f"(acc[3]) : "memory");
        asm volatile("st.shared.v4.f32 [%0], {%1,%2,%3,%4};" ::"r"(dn + 16), "f"(acc[4]), "f"(acc[5]), "f"(acc[6]), "f"(acc[7]) : "memory");
        named_bar(barid, 128);
        const uint32_t q = scr + tid * 16;
        st_word2(&g_Y2[dv][2 * tid],
                 pair_pack(lds32f(q) + lds32f(q + 2048), lds32f(q + 4) + lds32f(q + 2052), tag),
                 pair_pack(lds32f(q + 8) + lds32f(q + 2056), lds32f(q + 12) + lds32f(q + 2060), tag));
      }
      float v4[4] = {0.f, 0.f, 0.f, 0.f};
      if (tid < kDnUnits) {
        const uint64_t* pp = &g_Y2[tid][2 * c];
        uint64_t w0, w1;
        uint32_t spin = 0;
#pragma unroll 1
        while (true) {
          ll_raw2(pp, w0, w1);
          if (pair_ok(w0, tag) && pair_ok(w1, tag)) break;
          if (ll_backoff(spin, slp)) break;
        }
        v4[0] = pair_a(w0); v4[1] = pair_b(w0); v4[2] = pair_a(w1); v4[3] = pair_b(w1);
      }
      __syncwarp();
      fold<4>(v4, lane, 16);
      fold<2>(v4, lane, 8);
      float t2 = v4[0];
      t2 += __shfl_xor_sync(0xffffffffu, t2, 4);
      t2 += __shfl_xor_sync(0xffffffffu, t2, 2);
      t2 += __shfl_xor_sync(0xffffffffu, t2, 1);
      if ((lane & 7) == 0 && gw < 2) sts32f(scr + S_HH + (gw * 4 + 2 * (lane >> 4) + ((lane >> 3) & 1)) * 4, t2);
      named_bar(barid, 128);
      const int j = tid & 3;
      const float a = lds32f(scr + S_HH + j * 4) + lds32f(scr + S_HH + (4 + j) * 4);
      xown = bf16r(xown + bf16r(a));
      if (ch >= 2) {
        if (tid < 4) p.out[b * kD + 4 * c + tid] = __float2bfloat16_rn(xown);
      } else if (tid < 4) {
        ll_store(&g_X2[b][4 * c + tid], xown, tag);
        sts32f(sm + SM_XS + (b * 4 + tid) * 4, xown);
      }
      load_wq();
    } else {
      uint64_t wq4[4];
      pair_load4(wq4, &g_QP[4 * h][b * 64 + (tid >> 1)], 128, tag, slp);
      const int odd = tid & 1;
      const float qv = bf16r((pair_val(wq4[0], odd) + pair_val(wq4[1], odd)) + (pair_val(wq4[2], odd) + pair_val(wq4[3], odd)));
      const int kk = tid >> 4, r = tid & 15;
      const uint32_t off = (kk >> 1) * 64 + ((r & 7) >> 1) * 16 + (kk & 1) * 8 + (r >> 3) * 4 + (r & 1) * 2;
      sts16(sm + SM_Q + b * 256 + off, (uint16_t)(__float_as_uint(qv) >> 16));
      named_bar(barid, 128);
      if (tid == 0) mbar_arrive(sm + SM_BAR + (BAR_Q + b) * 8);
    }
  }
}

struct Acc { float o[4]; float m, l; };

__device__ __forceinline__ void qk_smem(float (&sa)[4], float (&sb)[4], uint32_t ka, uint32_t qa) {
#pragma unroll
  for (int kp = 0; kp < 4; ++kp) {
    const uint4 qf = lds128(qa + kp * 64);
    uint32_t a[4], a2[4];
    ldsm4(a, (ka ^ (((2 * kp) & 3) << 5)) + (kp >> 1) * 2048);
    ldsm4(a2, (ka ^ (((2 * kp + 1) & 3) << 5)) + (kp >> 1) * 2048);
    mma16816(sa, a, qf.x, qf.y);
    mma16816(sb, a2, qf.z, qf.w);
  }
}
__device__ __forceinline__ void k_load(uint32_t (&r)[8][4], uint32_t ka) {
#pragma unroll
  for (int kk = 0; kk < 8; ++kk) ldsm4(r[kk], (ka ^ ((kk & 3) << 5)) + (kk >> 2) * 2048);
}
__device__ __forceinline__ void qk_reg(float (&sa)[4], float (&sb)[4], const uint32_t (&r)[8][4], uint32_t qa) {
#pragma unroll
  for (int kp = 0; kp < 4; ++kp) {
    const uint4 qf = lds128(qa + kp * 64);
    mma16816(sa, r[2 * kp], qf.x, qf.y);
    mma16816(sb, r[2 * kp + 1], qf.z, qf.w);
  }
}
__device__ __forceinline__ void pv_smem(float (&o)[4], uint32_t va, uint32_t b0, uint32_t b1, int g) {
#pragma unroll
  for (int m = 0; m < 8; ++m) {
    uint32_t a[4];
    ldsm4t(a, (va ^ ((m & 3) << 5)) + (m >> 2) * 2048);
    mma16816(o, a, g == m ? b0 : 0u, g == m ? b1 : 0u);
  }
}
__device__ __forceinline__ void v_load(uint32_t (&r)[8][4], uint32_t va) {
#pragma unroll
  for (int m = 0; m < 8; ++m) ldsm4t(r[m], (va ^ ((m & 3) << 5)) + (m >> 2) * 2048);
}
__device__ __forceinline__ void pv_reg(float (&o)[4], const uint32_t (&r)[8][4], uint32_t b0, uint32_t b1, int g) {
#pragma unroll
  for (int m = 0; m < 8; ++m) mma16816(o, r[m], g == m ? b0 : 0u, g == m ? b1 : 0u);
}
__device__ __forceinline__ void write_partial(const Acc& a, uint32_t dst, int lane) {
  const int g = lane >> 2, t = lane & 3;
  float l = a.l;
  l += __shfl_xor_sync(0xffffffffu, l, 4);
  l += __shfl_xor_sync(0xffffffffu, l, 8);
  l += __shfl_xor_sync(0xffffffffu, l, 16);
  sts32f(dst + (32 * t + g) * 4, a.o[0]);
  sts32f(dst + (32 * t + 16 + g) * 4, a.o[1]);
  sts32f(dst + (32 * t + 8 + g) * 4, a.o[2]);
  sts32f(dst + (32 * t + 24 + g) * 4, a.o[3]);
  if (lane == 0) { sts32f(dst + 128 * 4, a.m); sts32f(dst + 129 * 4, l); }
}

template <int AUXREG, int CONREG>
__global__ void __launch_bounds__(kThreads, 1)
fused_kernel(const __grid_constant__ CUtensorMap tmK, const __grid_constant__ CUtensorMap tmV,
             const __grid_constant__ Params p) {
  const Sched& sc = c_sched;
  extern __shared__ __align__(1024) uint8_t smem_raw[];
  const uint32_t sm = smem_u32(smem_raw);
  const int warp = __shfl_sync(0xffffffffu, threadIdx.x >> 5, 0), lane = threadIdx.x & 31;
  const int c = blockIdx.x;
  auto load_epoch = [] {
    uint32_t e;
    asm volatile("ld.relaxed.gpu.global.u32 %0, [%1];" : "=r"(e) : "l"(&g_epoch) : "memory");
    return e;
  };

  if (warp >= 8) {
    if (lane < 2) {
      const int cw = (warp - 8) * 2 + lane;
      const uint32_t cbar = sm + SM_BAR + cw * 64, cring = sm + SM_RING + cw * 8192;
      const int crow = c * 4096 + cw * 16;
#pragma unroll
      for (int i = 0; i < 7; ++i) mbar_init(cbar + i * 8, 1);
      if (threadIdx.x == 256) {
        mbar_init(sm + SM_BAR + BAR_STAGE * 8, 8);
        mbar_init(sm + SM_BAR + BAR_Q * 8, 1);
        mbar_init(sm + SM_BAR + (BAR_Q + 1) * 8, 1);
        mbar_init(sm + SM_BAR + BAR_TAIL * 8, 8);
        mbar_init(sm + SM_BAR + BAR_PRE * 8, 1);
      }
      asm volatile("fence.mbarrier_init.release.cluster;" ::: "memory");
      asm volatile("fence.proxy.async;" ::: "memory");
      mbar_expect_tx(cbar, kTile);
      tma_tile(cring, &tmK, crow, cbar, kPolFirst);
      mbar_expect_tx(cbar + 8, kTile);
      tma_tile(cring + kTile, &tmV, crow, cbar + 8, kPolFirst);
    }
    __syncwarp();
    uint32_t tag = load_epoch();
    named_bar(0, kThreads);
    asm volatile("setmaxnreg.dec.sync.aligned.u32 %0;" ::"n"(AUXREG));
    asm volatile("add.u32 %0, %0, 1;" : "+r"(tag));
    if (lane < 2) {
      const int cw = (warp - 8) * 2 + lane;
      const uint32_t cbar = sm + SM_BAR + cw * 64, cret = sm + SM_RET + cw * 5 * kTile;
#pragma unroll
      for (int i = 0; i < kEarlyRet0; ++i) {
        if (i < 4 || cw != 7) {
          mbar_expect_tx(cbar + 16 + i * 8, kTile);
          tma_tile(cret + i * kTile, kRetIsV[i] ? &tmV : &tmK, c * 4096 + cw * 16 + kRetGrp[i] * 128, cbar + 16 + i * 8, kPolFirst);
        }
      }
    }
    __syncwarp();
    if ((c & 3) == 0 && threadIdx.x == 288) {
      for (int i = 0; i < 3; ++i) asm volatile("st.relaxed.gpu.global.u32 [%0], %1;" ::"l"(&g_claim[i][c >> 2]), "r"(0u) : "memory");
      __threadfence();
    }
#pragma unroll 1
    for (int ch = 0; ch < 4; ++ch) {
      int tid = threadIdx.x - 256;
      asm volatile("" : "+r"(tid));
      const int b = ch & 1;
      const bool fin = ch >= 2;
      const uint64_t wpol = (ch == 2) ? kPolNormal : kPolFirst;
      W16 w;
      if (ch < 3) mbar_wait(sm + SM_BAR + BAR_PRE * 8, b);
      w16_load<4 * kD * 2>(w, wo_ptr(p, c, tid), wpol);
      const float xres = fin ? lds32f(sm + SM_XS + (b * 4 + (tid & 3)) * 4) : __bfloat162float(p.x[b * kD + 4 * c + (tid & 3)]);
      if (ch < 3) {
        const int u = (c + 43 * ch) & 127, dv = dn_unit(u);
        if (tid < kPStride) st_word(&g_P[c][tid], 0);
        if (tid < 64) {
          st_word(&g_Y[c >> 2][(c & 3) * 64 + tid], 0);
          if (u < kGuUnits) st_word(&g_GU[u][tid], 0);
        }
        if (tid < 4) st_word(&g_X1[4 * c + tid], 0);
        if (dv >= 0) st_word2(&g_Y2[dv][2 * tid], 0, 0);
        if (ch < 2 && tid < 4) st_word(&g_X2[b][4 * c + tid], 0);
      }
      mbar_wait(sm + SM_BAR + (ch == 3 ? BAR_TAIL : BAR_STAGE) * 8, ch == 3 ? 0 : b);
      glue(p, ch, make_tag(tag, 1 + ch), tid, sm, ch == 3 ? sm + SM_RING : sm + SM_STAGE, ch == 3 ? 8192 : kStageStride * 4, xres, w, wpol);
    }
    if (c == 0 && threadIdx.x == 256) g_epoch = tag;
  } else {
    const int h = c >> 2;
    const int tb = (warp == 7) ? 1 : 0;
    const uint32_t ringK = sm + SM_RING + warp * 8192, ringV = ringK + 4096;
    const uint32_t ret0 = sm + SM_RET + warp * 5 * kTile;
    const uint32_t bar0 = sm + SM_BAR + warp * 64;
    const int rowBase = c * 4096 + warp * 16;

    {
      const int s = c & 3, hf = warp >> 2, rb = warp & 3, rsub = lane >> 3;
      uint4 w[8];
      ldw_rows<4 * kH * kDh * 2, 8>(
          w, p.wq + (size_t)(128 * s + 32 * rb + rsub) * (kH * kDh) + h * kDh + 64 * hf + 8 * (lane & 7), kPolFirst);
      uint4 xa[2][2];
      uint16_t xo[2];
#pragma unroll
      for (int b = 0; b < 2; ++b) {
        xa[b][0] = ldw(p.x + b * kD + lane * 16, kPolNormal);
        xa[b][1] = ldw(p.x + b * kD + lane * 16 + 8, kPolNormal);
        asm volatile("ld.global.nc.u16 %0, [%1];" : "=h"(xo[b]) : "l"(p.x + b * kD + 128 * s + 32 * rb + lane));
      }
      uint32_t tag = load_epoch();
      named_bar(0, kThreads);
      asm volatile("setmaxnreg.inc.sync.aligned.u32 %0;" ::"n"(CONREG));
      asm volatile("add.u32 %0, %0, 1;" : "+r"(tag));
      float xn[2];
#pragma unroll
      for (int b = 0; b < 2; ++b) {
        const uint32_t u[8] = {xa[b][0].x, xa[b][0].y, xa[b][0].z, xa[b][0].w, xa[b][1].x, xa[b][1].y, xa[b][1].z, xa[b][1].w};
        float sum = 0.f;
#pragma unroll
        for (int i = 0; i < 8; ++i) sum += bflo(u[i]) + bfhi(u[i]);
        const float mean = warp_sum(sum) * (1.0f / kD);
        float q = 0.f;
#pragma unroll
        for (int i = 0; i < 8; ++i) {
          const float d0 = bflo(u[i]) - mean, d1 = bfhi(u[i]) - mean;
          q = fmaf(d0, d0, fmaf(d1, d1, q));
        }
        const float var = warp_sum(q) * (1.0f / kD);
        const float sd = bf16r(sqrtf(bf16r(bf16r(var) + 1e-5f)));
        xn[b] = bf16r(bf16r(__uint_as_float((uint32_t)xo[b] << 16) - bf16r(mean)) * __frcp_rn(sd));
      }
      float acc0[8], acc1[8];
#pragma unroll
      for (int i = 0; i < 8; ++i) { acc0[i] = 0.f; acc1[i] = 0.f; }
#pragma unroll
      for (int j = 0; j < 8; ++j) {
        fma8(acc0, w[j], __shfl_sync(0xffffffffu, xn[0], 4 * j + rsub));
        fma8(acc1, w[j], __shfl_sync(0xffffffffu, xn[1], 4 * j + rsub));
      }
      fold<8>(acc0, lane, 16); fold<4>(acc0, lane, 8);
      fold<8>(acc1, lane, 16); fold<4>(acc1, lane, 8);
      const uint32_t red = sm + SM_STAGE + (rb * 128 + hf * 64 + (lane & 7) * 8 + ((lane >> 4) & 1) * 4 + ((lane >> 3) & 1) * 2) * 4;
      sts32f(red, acc0[0]); sts32f(red + 4, acc0[1]);
      sts32f(red + 2048, acc1[0]); sts32f(red + 2052, acc1[1]);
      named_bar(1, 256);
      const int t = threadIdx.x, qb = t >> 7, d = t & 127;
      const uint32_t r = sm + SM_STAGE + qb * 2048 + d * 4;
      tag = make_tag(tag, 0);
      pair_publish(&g_QP[c][0], t, (lds32f(r) + lds32f(r + 512)) + (lds32f(r + 1024) + lds32f(r + 1536)), tag);
      {
        uint64_t w4[4];
        pair_load4(w4, &g_QP[4 * h][t >> 1], 128, tag, 32);
        const int odd = t & 1;
        const float qv = bf16r((pair_val(w4[0], odd) + pair_val(w4[1], odd)) + (pair_val(w4[2], odd) + pair_val(w4[3], odd)));
        const int kk = d >> 4, rr = d & 15;
        const uint32_t off = (kk >> 1) * 64 + ((rr & 7) >> 1) * 16 + (kk & 1) * 8 + (rr >> 3) * 4 + (rr & 1) * 2;
        sts16(sm + SM_Q + qb * 256 + off, (uint16_t)(__float_as_uint(qv) >> 16));
      }
      if (lane == 0) {
        for (int i = kEarlyRet0; i < (warp == 7 ? 4 : 5); ++i) {
          mbar_expect_tx(bar0 + 16 + i * 8, kTile);
          tma_tile(ret0 + i * kTile, kRetIsV[i] ? &tmV : &tmK, rowBase + kRetGrp[i] * 128, bar0 + 16 + i * 8, kPolFirst);
        }
      }
      named_bar(1, 256);
    }

    const int g = lane >> 2, t = lane & 3, mi = lane >> 3, l7 = lane & 7;
    const uint32_t offK = (l7 + 8 * (mi & 1)) * 128 + (((mi >> 1) ^ l7) << 4);
    const uint32_t offV = (l7 + 8 * (mi >> 1)) * 128 + (((mi & 1) ^ l7) << 4);
    const uint32_t qa0 = sm + SM_Q + t * 16;
    constexpr float kInvSqrtDh = 0.08838834764831845f, kLog2e = 1.4426950408889634f;
    uint32_t kr0[8][4], kr1[8][4], kr2[8][4], vr0[8][4], vr1[8][4];
#pragma unroll
    for (int i = 0; i < 8; ++i)
#pragma unroll
      for (int j = 0; j < 4; ++j) { kr0[i][j] = 0; kr1[i][j] = 0; kr2[i][j] = 0; vr0[i][j] = 0; vr1[i][j] = 0; }
    Acc cur, oth;
#pragma unroll
    for (int i = 0; i < 4; ++i) { cur.o[i] = 0.f; oth.o[i] = 0.f; }
    cur.m = -INFINITY; cur.l = 0.f; oth.m = -INFINITY; oth.l = 0.f;
    uint32_t kph = 0, vph = 0;

    const int nSteps = sc.nSteps;
    uint32_t pend = 0;
    int st = 0;
#pragma unroll 1
    while (true) {
      const Step d = sc.step[tb][st];
      const uint32_t ctl = d.x;
      const uint32_t b = ctl & C_B;
      int dynRow = -1;
      if (ctl & (C_CLAIM0 | C_DYN)) {
        const int pl = (ctl >> C_POOL_SH) & 3;
        bool claim = true;
        if (ctl & C_DYN) {
          const uint32_t n = __shfl_sync(0xffffffffu, pend, 0);
          claim = n < sc.poolSize[pl];
          if (claim) dynRow = (b * kH + h) * kSk + ((n >> 3) & 3) * 4096 + ((sc.poolGrp[pl] + (n >> 5)) * 8 + (n & 7)) * 16;
        }
        if (claim && lane == 0) pend = atomicAdd(&g_claim[pl][h], 1u);
      }
      if (ctl & C_SWAP) { Acc tmp = cur; cur = oth; oth = tmp; }
      if (ctl & C_RESET) {
        cur.o[0] = cur.o[1] = cur.o[2] = cur.o[3] = 0.f;
        cur.m = -INFINITY; cur.l = 0.f;
      }
      if (ctl & C_WAITQ) mbar_wait(sm + SM_BAR + (BAR_Q + b) * 8, 0);
      const uint32_t qa = qa0 + b * 256;
      float sa[4] = {0.f, 0.f, 0.f, 0.f}, sb[4] = {0.f, 0.f, 0.f, 0.f};
      {
        const uint32_t kreg = (ctl >> C_KREG_SH) & 3, kslot = (ctl >> C_KSLOT_SH) & 7;
        const bool ksm = (ctl >> C_KSM_SH) & 1;
        const uint32_t kaddr = kslot ? ret0 + (kslot - 1) * kTile : ringK;
        const uint32_t kbar = kslot ? bar0 + 8 + kslot * 8 : bar0;
        if (ksm) {
          mbar_wait(kbar, kslot ? b : kph);
          if (!kslot) kph ^= 1;
        }
        const uint32_t ka = kaddr + offK;
        if (kreg == 0) {
          qk_smem(sa, sb, ka, qa);
        } else if (kreg == 1) {
          if (ksm) k_load(kr0, ka);
          qk_reg(sa, sb, kr0, qa);
        } else if (kreg == 2) {
          if (ksm) k_load(kr1, ka);
          qk_reg(sa, sb, kr1, qa);
        } else {
          if (ksm) k_load(kr2, ka);
          qk_reg(sa, sb, kr2, qa);
        }
        const uint32_t ik = d.y & 0xff;
        if ((ik & I_VALID) || dynRow >= 0) {
          __syncwarp();
          if (lane == 0) {
            const int row = dynRow >= 0 ? dynRow : rowBase + ((ik & I_B) ? kH * kSk : 0) + (ik & 31) * 128;
            mbar_expect_tx(kbar, kTile);
            tma_tile(kaddr, &tmK, row, kbar, kPolFirst);
            if (ik & I_KEEP) l2_keep_tile(p.k + (size_t)row * kDh);
          }
        }
      }
      const float t0 = bf16r(bf16r(sa[0] + sb[0]) * kInvSqrtDh) * kLog2e;
      const float t1 = bf16r(bf16r(sa[2] + sb[2]) * kInvSqrtDh) * kLog2e;
      float mx = fmaxf(t0, t1);
      mx = fmaxf(mx, __shfl_xor_sync(0xffffffffu, mx, 4));
      mx = fmaxf(mx, __shfl_xor_sync(0xffffffffu, mx, 8));
      mx = fmaxf(mx, __shfl_xor_sync(0xffffffffu, mx, 16));
      if (mx > cur.m) {
        const float f = ex2(cur.m - mx);
        cur.l *= f;
        cur.o[0] *= f; cur.o[1] *= f; cur.o[2] *= f; cur.o[3] *= f;
        cur.m = mx;
      }
      const float p0 = ex2(t0 - cur.m), p1 = ex2(t1 - cur.m);
      cur.l += p0 + p1;
      const uint32_t b0 = movm(pack_bf16x2(p0, p0)), b1 = movm(pack_bf16x2(p1, p1));
      {
        const uint32_t vreg = (ctl >> C_VREG_SH) & 3, vslot = (ctl >> C_VSLOT_SH) & 7;
        const bool vsm = (ctl >> C_VSM_SH) & 1;
        const uint32_t vaddr = vslot ? ret0 + (vslot - 1) * kTile : ringV;
        const uint32_t vbar = vslot ? bar0 + 8 + vslot * 8 : bar0 + 8;
        if (vsm) {
          mbar_wait(vbar, vslot ? b : vph);
          if (!vslot) vph ^= 1;
        }
        const uint32_t va = vaddr + offV;
        if (vreg == 0) {
          pv_smem(cur.o, va, b0, b1, g);
        } else if (vreg == 1) {
          if (vsm) v_load(vr0, va);
          pv_reg(cur.o, vr0, b0, b1, g);
        } else {
          if (vsm) v_load(vr1, va);
          pv_reg(cur.o, vr1, b0, b1, g);
        }
        const uint32_t iv = (d.y >> 8) & 0xff;
        if ((iv & I_VALID) || dynRow >= 0) {
          __syncwarp();
          if (lane == 0) {
            const int row = dynRow >= 0 ? dynRow : rowBase + ((iv & I_B) ? kH * kSk : 0) + (iv & 31) * 128;
            mbar_expect_tx(vbar, kTile);
            tma_tile(vaddr, &tmV, row, vbar, kPolFirst);
            if (iv & I_KEEP) l2_keep_tile(p.v + (size_t)row * kDh);
          }
        }
      }
      if ((ctl & C_PREW) && threadIdx.x == 0) mbar_arrive(sm + SM_BAR + BAR_PRE * 8);
      if ((ctl & (C_PUB | C_PUBO)) && dynRow < 0) {
        Acc pub;
        const bool po = ctl & C_PUBO;
        pub.o[0] = po ? oth.o[0] : cur.o[0]; pub.o[1] = po ? oth.o[1] : cur.o[1];
        pub.o[2] = po ? oth.o[2] : cur.o[2]; pub.o[3] = po ? oth.o[3] : cur.o[3];
        pub.m = po ? oth.m : cur.m; pub.l = po ? oth.l : cur.l;
        write_partial(pub, sm + SM_STAGE + warp * kStageStride * 4, lane);
        __syncwarp();
        if (lane == 0) mbar_arrive(sm + SM_BAR + BAR_STAGE * 8);
      }
      if (dynRow < 0 && ++st == nSteps) break;
    }

    write_partial(cur, ringK, lane);
    __syncwarp();
    if (lane == 0) mbar_arrive(sm + SM_BAR + BAR_TAIL * 8);
  }
}

typedef CUresult (*EncodeTiledFn)(CUtensorMap*, CUtensorMapDataType, cuuint32_t, void*, const cuuint64_t*,
                                  const cuuint64_t*, const cuuint32_t*, const cuuint32_t*, CUtensorMapInterleave,
                                  CUtensorMapSwizzle, CUtensorMapL2promotion, CUtensorMapFloatOOBfill);

void make_map(CUtensorMap* tm, EncodeTiledFn enc, void* base) {
  cuuint64_t dims[3] = {64, (cuuint64_t)2 * kH * kSk, 2};
  cuuint64_t strides[2] = {256, 128};
  cuuint32_t box[3] = {64, 16, 2};
  cuuint32_t es[3] = {1, 1, 1};
  enc(tm, CU_TENSOR_MAP_DATA_TYPE_BFLOAT16, 3, base, dims, strides, box, es, CU_TENSOR_MAP_INTERLEAVE_NONE,
      CU_TENSOR_MAP_SWIZZLE_128B, CU_TENSOR_MAP_L2_PROMOTION_NONE, CU_TENSOR_MAP_FLOAT_OOB_FILL_NONE);
}


}

extern "C" void kernel_launch(void* const* d_in, const int* in_sizes, int n_in, void* d_out, int out_size) {
  (void)in_sizes; (void)n_in; (void)out_size;
  static EncodeTiledFn enc = nullptr;
  auto kern = fused_kernel<88, 208>;
  if (!enc) {
    cudaDriverEntryPointQueryResult qr;
    cudaGetDriverEntryPoint("cuTensorMapEncodeTiled", (void**)&enc, cudaEnableDefault, &qr);
    cudaFuncSetAttribute(kern, cudaFuncAttributeMaxDynamicSharedMemorySize, SM_TOTAL);
  }
  CUtensorMap tmK, tmV;
  make_map(&tmK, enc, d_in[1]);
  make_map(&tmV, enc, d_in[2]);
  Params p;
  p.x = (const __nv_bfloat16*)d_in[0];
  p.k = (const __nv_bfloat16*)d_in[1];
  p.v = (const __nv_bfloat16*)d_in[2];
  p.wq = (const __nv_bfloat16*)d_in[3];
  p.wo = (const __nv_bfloat16*)d_in[4];
  p.wg = (const __nv_bfloat16*)d_in[6];
  p.wu = (const __nv_bfloat16*)d_in[7];
  p.wd = (const __nv_bfloat16*)d_in[8];
  p.out = (__nv_bfloat16*)d_out;
  kern<<<kCtas, kThreads, SM_TOTAL, cudaStreamPerThread>>>(tmK, tmV, p);
}
```
